```python
import torch

def _softmax(x, axis=-1):
    return torch.softmax(x, dim=axis)

def _gelu(x):
    return torch.nn.functional.gelu(x, approximate='tanh')

def _silu(x):
    return torch.nn.functional.silu(x)

def _sigmoid(x):
    return torch.sigmoid(x)

def _layernorm(x, axis=-1, eps=1e-05):
    m = x.mean(dim=axis, keepdim=True)
    v = x.var(dim=axis, keepdim=True, unbiased=False)
    return (x - m) / torch.sqrt(v + eps)

def _scatter_add(tgt, idx, src, axis=0):
    return tgt.clone().index_add_(axis, idx, src)

def _segment_sum(src, seg, n):
    out = torch.zeros((n,) + src.shape[1:], dtype=src.dtype)
    return out.index_add_(0, seg, src)

def _pad(x, pw):
    flat = tuple((v for pair in reversed(pw) for v in pair))
    return torch.nn.functional.pad(x, flat)
kernel_name = 'standalone__molecular_angular_painn__graph'

def setup_inputs():

    _w = lambda a: (lambda t: t.to(torch.bfloat16) if t.is_floating_point() else t)(torch.as_tensor(a))
    N, deg, D = (10000, 64, 64)
    n_rbf = max(16, 4)
    E = N * deg
    cutoff = 5.0
    freqs = (torch.arange(1, n_rbf + 1) * torch.pi / cutoff).to(float)
    return {'sv': _w((lambda *s: torch.randn(*s, dtype=torch.bfloat16) * 0.4)(N, 4, D) * 0.3), 'pos': _w((lambda *s: torch.randn(*s, dtype=torch.bfloat16) * 1.6)(N, 3) * 1.2), 'src': _w((lambda lo, hi, *s: torch.randint(lo, hi, s))(0, N, E).to(torch.int64)), 'dst': _w((lambda lo, hi, *s: torch.randint(lo, hi, s))(0, N, E).to(torch.int64)), 'freqs': _w(freqs), 'w_phi1': _w((lambda *s: torch.randn(*s, dtype=torch.bfloat16) * 3.2)(D, D) / D ** 0.5), 'w_phi2': _w((lambda *s: torch.randn(*s, dtype=torch.bfloat16) * 1.6)(D, 3 * D) / D ** 0.5), 'w_rbf': _w((lambda *s: torch.randn(*s, dtype=torch.bfloat16) * 1.6)(n_rbf, 3 * D) / n_rbf ** 0.5)}

def reference(sv, pos, src, dst, freqs, w_phi1, w_phi2, w_rbf):
    N, _, D = sv.shape
    E = src.shape[0]
    PI, cutoff = (3.141592653589793, 5.0)
    s, v = (sv[:, 0, :].clone(), sv[:, 1:, :].clone())
    r_vec = pos[src] - pos[dst]
    d = torch.sqrt((r_vec * r_vec).sum(-1) + 1e-08)
    r_hat = r_vec / d[:, None]
    rbf = torch.sin(d[:, None] * freqs[None, :]) / d[:, None]
    fcut = 0.5 * (torch.cos(PI * d / cutoff) + 1.0)
    fcut = torch.where(d < cutoff, fcut, 0.0 * d)
    Wf = rbf @ w_rbf * fcut[:, None]
    phi = (_silu(s @ w_phi1) @ w_phi2)[src]
    m = phi * Wf
    m_s, m_vv, m_vr = (m[:, :D].clone(), m[:, D:2 * D].clone(), m[:, 2 * D:].clone())
    ds = _segment_sum(m_s, dst, N)
    dv_e = m_vv[:, None, :] * v[src] + m_vr[:, None, :] * r_hat[:, :, None]
    dv = _segment_sum(dv_e.reshape(E, 3 * D), dst, N).reshape(N, 3, D)
    return sv + torch.concatenate([ds[:, None, :], dv], axis=1)
```

```cpp
#include <cuda_runtime.h>
#include <cuda_bf16.h>
#include <stdint.h>

namespace {

constexpr int NN = 10000;
constexpr int EE = 640000;
constexpr int NT = 512;
constexpr int NEWW = 11;
constexpr int NEW_ = NEWW * 32;
constexpr int MAXP = 160;
constexpr int CAPR = 72;
constexpr int RUNB = CAPR * 4;
constexpr int NTILES = NN / 16;
constexpr int NTILEW = 5;
constexpr int BKT_ENTRIES = 7296;

constexpr int NSLOT     = 6;
constexpr int ROWB      = 640;
constexpr int SLOTB     = 5 * 2048;
constexpr int SM_RING   = 0;
constexpr int SM_COEF   = 2 * NSLOT * SLOTB;
constexpr int SM_BKT    = SM_COEF + 2 * NSLOT * 2048;
constexpr int LUT_BASE = 0x3E80, LUT_N = 0x40A0 - 0x3E80;
constexpr int SM_LUT    = SM_BKT + BKT_ENTRIES * 8;
constexpr int SM_GL     = SM_LUT + LUT_N * 32;
constexpr int SM_HIST   = SM_GL + 2048;
constexpr int SM_CNT    = SM_HIST + 640;
constexpr int SM_MISC   = SM_CNT + 528;
constexpr int SM_BAR    = SM_MISC + 128;
constexpr int SM_TOTAL  = SM_BAR + 26 * 8;
constexpr int SM_ALLOC  = SM_TOTAL + 1024 + 128 + 4096;
constexpr int SM_POS    = 0;
constexpr int SM_RUNS   = 60032;
constexpr int SM_W2P    = SM_RUNS + MAXP * RUNB;
constexpr int WSTRIDE   = 400;
constexpr int SM_WRP    = SM_W2P + 64 * WSTRIDE;
constexpr int SM_W1S    = SM_WRP + 16 * WSTRIDE;
constexpr int W1STRIDE  = 144;
constexpr int SM_TILE   = SM_BKT;
constexpr int TILE_STRIDE = 656;
constexpr int TILE_BYTES  = 16 * TILE_STRIDE;
static_assert(SM_ALLOC <= 232448, "smem");
static_assert(NTILEW * TILE_BYTES <= BKT_ENTRIES * 8, "tiles");
static_assert(SM_W1S + 64 * W1STRIDE <= SM_BKT, "weights");

constexpr int MISC_EPOCH = 8;
constexpr int MISC_GSPLIT = 9;
constexpr int MISC_GTOT = 10;
constexpr int MISC_NSPLIT = 11;
constexpr int MISC_WT2 = 12;
constexpr int MISC_QN = 16;
constexpr int MISC_OVF = 17;
constexpr int MISC_DONE = 18;

constexpr int SPIN_LIMIT = 1 << 22;

__device__ __align__(1024) __nv_bfloat16 g_table[NN * 320];
__device__ __align__(128) uint32_t g_stage[MAXP * MAXP * CAPR];
__device__ unsigned g_barA;
__device__ unsigned g_barB;
#define STAMP(s, cond) do {} while (0)
#define STAMP_DUMP() do {} while (0)

#define CYC_DECL do {} while (0)
#define CYC(i) do {} while (0)
#define CYC_DUMP() do {} while (0)
#define TRACE(gq, k) do {} while (0)
struct Params {
    const __nv_bfloat16* sv;
    const __nv_bfloat16* pos;
    const int* src;
    const int* dst;
    const __nv_bfloat16* freqs;
    const __nv_bfloat16* w1;
    const __nv_bfloat16* w2;
    const __nv_bfloat16* wr;
    __nv_bfloat16* out;
    int nper;
    unsigned magic;
    int e4q;
    int capn;
};

__device__ __forceinline__ uint32_t smem_u32(const void* p) { return (uint32_t)__cvta_generic_to_shared(p); }
__device__ __forceinline__ void mbar_init(uint32_t bar, uint32_t cnt) {
    asm volatile("mbarrier.init.shared.b64 [%0], %1;" :: "r"(bar), "r"(cnt) : "memory");
}
__device__ __forceinline__ void mbar_arrive_elect(uint32_t bar) {
    asm volatile("{\n.reg .pred p;\nelect.sync _|p, 0xffffffff;\n@p mbarrier.arrive.shared.b64 _, [%0];\n}" :: "r"(bar) : "memory");
}
__device__ __forceinline__ bool mbar_try(uint32_t bar, uint32_t parity) {
    uint32_t ok;
    asm volatile("{\n.reg .pred p;\nmbarrier.try_wait.parity.shared.b64 p, [%1], %2;\nselp.u32 %0, 1, 0, p;\n}"
                 : "=r"(ok) : "r"(bar), "r"(parity) : "memory");
    return ok != 0;
}
__device__ __forceinline__ void mbar_wait(uint32_t bar, uint32_t parity) {
    int it = 0;
    while (!mbar_try(bar, parity)) { if (++it > SPIN_LIMIT) __trap(); }
}
__device__ __forceinline__ void cp_async16(uint32_t dst, const void* src) {
    asm volatile("cp.async.cg.shared.global [%0], [%1], 16;" :: "r"(dst), "l"(src) : "memory");
}
__device__ __forceinline__ void cp_async16_zfill(uint32_t dst, const void* src, int sz) {
    asm volatile("cp.async.cg.shared.global [%0], [%1], 16, %2;" :: "r"(dst), "l"(src), "r"(sz) : "memory");
}
__device__ __forceinline__ void cp_async16_valid(uint32_t dst, const void* src, uint32_t s) {
    asm volatile("{\n.reg .pred p;\nsetp.ne.u32 p, %2, 0xffffffff;\n@p cp.async.cg.shared.global [%0], [%1], 16;\n}"
                 :: "r"(dst), "l"(src), "r"(s) : "memory");
}
__device__ __forceinline__ void cp_async_arrive_noinc(uint32_t bar) {
    asm volatile("cp.async.mbarrier.arrive.noinc.shared.b64 [%0];" :: "r"(bar) : "memory");
}
__device__ __forceinline__ void fence_proxy_async() { asm volatile("fence.proxy.async.shared::cta;" ::: "memory"); }
__device__ __forceinline__ void ldsm_x4(uint32_t (&r)[4], uint32_t addr) {
    asm volatile("ldmatrix.sync.aligned.m8n8.x4.shared.b16 {%0,%1,%2,%3}, [%4];"
                 : "=r"(r[0]), "=r"(r[1]), "=r"(r[2]), "=r"(r[3]) : "r"(addr) : "memory");
}
__device__ __forceinline__ void ldsm_x4_t(uint32_t (&r)[4], uint32_t addr) {
    asm volatile("ldmatrix.sync.aligned.m8n8.x4.trans.shared.b16 {%0,%1,%2,%3}, [%4];"
                 : "=r"(r[0]), "=r"(r[1]), "=r"(r[2]), "=r"(r[3]) : "r"(addr) : "memory");
}
__device__ __forceinline__ void stsm_x4(uint32_t addr, uint32_t r0, uint32_t r1, uint32_t r2, uint32_t r3) {
    asm volatile("stmatrix.sync.aligned.m8n8.x4.shared.b16 [%0], {%1,%2,%3,%4};"
                 :: "r"(addr), "r"(r0), "r"(r1), "r"(r2), "r"(r3) : "memory");
}
__device__ __forceinline__ void mma16816(float (&c)[4], const uint32_t (&a)[4], uint32_t b0, uint32_t b1) {
    asm volatile("mma.sync.aligned.m16n8k16.row.col.f32.bf16.bf16.f32 {%0,%1,%2,%3}, {%4,%5,%6,%7}, {%8,%9}, {%0,%1,%2,%3};"
                 : "+f"(c[0]), "+f"(c[1]), "+f"(c[2]), "+f"(c[3])
                 : "r"(a[0]), "r"(a[1]), "r"(a[2]), "r"(a[3]), "r"(b0), "r"(b1));
}
__device__ __forceinline__ void mma16816_z(float (&c)[4], const uint32_t (&a)[4], uint32_t b0, uint32_t b1) {
    asm volatile("mma.sync.aligned.m16n8k16.row.col.f32.bf16.bf16.f32 {%0,%1,%2,%3}, {%4,%5,%6,%7}, {%8,%9}, {%10,%10,%10,%10};"
                 : "=f"(c[0]), "=f"(c[1]), "=f"(c[2]), "=f"(c[3])
                 : "r"(a[0]), "r"(a[1]), "r"(a[2]), "r"(a[3]), "r"(b0), "r"(b1), "f"(0.f));
}
__device__ __forceinline__ uint32_t lds16(uint32_t a) { unsigned short v; asm volatile("ld.shared.u16 %0, [%1];" : "=h"(v) : "r"(a) : "memory"); return v; }
__device__ __forceinline__ uint32_t lds32(uint32_t a) { uint32_t v; asm volatile("ld.shared.u32 %0, [%1];" : "=r"(v) : "r"(a) : "memory"); return v; }
__device__ __forceinline__ uint2 lds64(uint32_t a) { uint2 v; asm volatile("ld.shared.v2.u32 {%0,%1}, [%2];" : "=r"(v.x), "=r"(v.y) : "r"(a) : "memory"); return v; }
__device__ __forceinline__ uint4 lds128(uint32_t a) { uint4 v; asm volatile("ld.shared.v4.u32 {%0,%1,%2,%3}, [%4];" : "=r"(v.x), "=r"(v.y), "=r"(v.z), "=r"(v.w) : "r"(a) : "memory"); return v; }
__device__ __forceinline__ void sts16(uint32_t a, uint32_t v) { asm volatile("st.shared.u16 [%0], %1;" :: "r"(a), "h"((unsigned short)v) : "memory"); }
__device__ __forceinline__ void sts32(uint32_t a, uint32_t v) { asm volatile("st.shared.u32 [%0], %1;" :: "r"(a), "r"(v) : "memory"); }
__device__ __forceinline__ void sts64(uint32_t a, uint32_t x, uint32_t y) { asm volatile("st.shared.v2.u32 [%0], {%1,%2};" :: "r"(a), "r"(x), "r"(y) : "memory"); }
__device__ __forceinline__ void sts128(uint32_t a, uint4 v) { asm volatile("st.shared.v4.u32 [%0], {%1,%2,%3,%4};" :: "r"(a), "r"(v.x), "r"(v.y), "r"(v.z), "r"(v.w) : "memory"); }
__device__ __forceinline__ int4 ldg_stream(const int4* p) {
    int4 v;
    asm volatile("ld.global.nc.L1::no_allocate.v4.s32 {%0,%1,%2,%3}, [%4];" : "=r"(v.x), "=r"(v.y), "=r"(v.z), "=r"(v.w) : "l"(p));
    return v;
}
__device__ __forceinline__ uint4 ld_ca_128(const uint4* p) {
    uint4 v; asm volatile("ld.global.ca.v4.u32 {%0,%1,%2,%3}, [%4];" : "=r"(v.x), "=r"(v.y), "=r"(v.z), "=r"(v.w) : "l"(p) : "memory"); return v;
}
__device__ __forceinline__ unsigned ld_acquire(const unsigned* p) {
    unsigned v; asm volatile("ld.acquire.gpu.global.u32 %0, [%1];" : "=r"(v) : "l"(p) : "memory"); return v;
}
__device__ __forceinline__ unsigned atom_add_release(unsigned* p, unsigned v) {
    unsigned o; asm volatile("atom.add.release.gpu.global.u32 %0, [%1], %2;" : "=r"(o) : "l"(p), "r"(v) : "memory"); return o;
}
__device__ __forceinline__ unsigned ld_relaxed(const unsigned* p) {
    unsigned v; asm volatile("ld.relaxed.gpu.global.u32 %0, [%1];" : "=r"(v) : "l"(p) : "memory"); return v;
}
__device__ __forceinline__ void red_add_release(unsigned* p, unsigned v) {
    asm volatile("red.add.release.gpu.global.u32 [%0], %1;" :: "l"(p), "r"(v) : "memory");
}
__device__ __forceinline__ void wait_counter(const unsigned* p, unsigned target) {
    int it = 0;
    while ((int)(ld_acquire(p) - target) < 0) { if (++it > SPIN_LIMIT) __trap(); }
}
template <int ID, int N> __device__ __forceinline__ void bar_sync() { asm volatile("bar.sync %0, %1;" :: "n"(ID), "n"(N) : "memory"); }
template <int ID, int N> __device__ __forceinline__ void bar_arrive() { asm volatile("bar.arrive %0, %1;" :: "n"(ID), "n"(N) : "memory"); }

__device__ __forceinline__ float bf_lo(uint32_t x) { return __uint_as_float(x << 16); }
__device__ __forceinline__ float bf_hi(uint32_t x) { return __uint_as_float(x & 0xFFFF0000u); }
__device__ __forceinline__ uint32_t pack_bf2(float lo, float hi) {
    uint32_t r; asm("cvt.rn.bf16x2.f32 %0, %1, %2;" : "=r"(r) : "f"(hi), "f"(lo)); return r;
}
__device__ __forceinline__ float rbf(float x) { return bf_hi(pack_bf2(0.f, x)); }
__device__ __forceinline__ uint32_t hmul2_bf(uint32_t a, uint32_t b) {
    uint32_t r; asm("mul.rn.bf16x2 %0, %1, %2;" : "=r"(r) : "r"(a), "r"(b)); return r;
}
__device__ __forceinline__ uint32_t hfma2_bf(uint32_t a, uint32_t b, uint32_t c) {
    uint32_t r; asm("fma.rn.bf16x2 %0, %1, %2, %3;" : "=r"(r) : "r"(a), "r"(b), "r"(c)); return r;
}
__device__ __forceinline__ uint32_t hsub2_bf(uint32_t a, uint32_t b) {
    uint32_t r; asm("sub.rn.bf16x2 %0, %1, %2;" : "=r"(r) : "r"(a), "r"(b)); return r;
}
__device__ __forceinline__ float sqrt_apx(float x) { float r; asm("sqrt.approx.ftz.f32 %0, %1;" : "=f"(r) : "f"(x)); return r; }
__device__ __forceinline__ float rcp_apx(float x) { float r; asm("rcp.approx.ftz.f32 %0, %1;" : "=f"(r) : "f"(x)); return r; }

__device__ __forceinline__ float edge_dist(uint32_t rxy, uint32_t rz  ) {
    uint32_t sq = hmul2_bf(rxy, rxy);
    uint32_t sz = hmul2_bf(rz, rz);
    float ss = rbf((bf_lo(sq) + bf_hi(sq)) + bf_lo(sz));
    ss = rbf(ss + 1e-8f);
    return rbf(sqrt_apx(ss));
}
__device__ __forceinline__ float edge_fcut(float d) {
    float t = rbf(d * 3.14159265358979f);
    t = rbf(t * 0.2f);
    float c = rbf(__cosf(t));
    return 0.5f * rbf(c + 1.0f);
}

__device__ __forceinline__ void load_pos(uint32_t base, int n, uint32_t& xy, uint32_t& z) {
    uint32_t a = base + ((n * 6) & ~3);
    uint32_t w0 = lds32(a), w1 = lds32(a + 4);
    uint32_t sh = (n & 1) << 4;
    xy = __funnelshift_r(w0, w1, sh);
    z = (w1 >> sh) & 0xFFFFu;
}

__device__ __forceinline__ void unpack8(float (&x)[8], const uint32_t (&p)[4]) {
#pragma unroll
    for (int i = 0; i < 4; i++) {
        uint32_t v = p[i];
        asm volatile("" : "+r"(v));
        x[2 * i] = bf_lo(v); x[2 * i + 1] = bf_hi(v);
    }
}

#define CWAIT(a, b) mbar_wait(a, b)
__device__ __forceinline__ void wg_fence() { asm volatile("wgmma.fence.sync.aligned;" ::: "memory"); }
__device__ __forceinline__ void wg_commit() { asm volatile("wgmma.commit_group.sync.aligned;" ::: "memory"); }
template <int N> __device__ __forceinline__ void wg_wait() { asm volatile("wgmma.wait_group.sync.aligned %0;" :: "n"(N) : "memory"); }
constexpr uint32_t DESC_HI = (1u << 30) | (1024u >> 4);
__device__ __forceinline__ uint32_t desc_lo(uint32_t addr) { return ((addr & 0x3FFFF) >> 4) | (1u << 16); }

#define R8(C, d, o) C(d[o]), C(d[o + 1]), C(d[o + 2]), C(d[o + 3]), C(d[o + 4]), C(d[o + 5]), C(d[o + 6]), C(d[o + 7])
#define WG_PRED_FIRST "setp.ne.b32 p, 0, 0;\n"
#define WG_PRED_ACC   "setp.eq.b32 p, 0, 0;\n"
#define DEF_WG_SS64(NAME, C, PRED)                                                                              \
__device__ __forceinline__ void NAME(float (&d)[32], uint32_t da, uint32_t db) {                                \
    asm volatile("{\n.reg .pred p;\n.reg .b64 da, db;\n" PRED "mov.b64 da, {%32, %34};\nmov.b64 db, {%33, %34};\n"  \
        "wgmma.mma_async.sync.aligned.m64n64k16.f32.bf16.bf16 "                                                 \
        "{%0,%1,%2,%3,%4,%5,%6,%7,%8,%9,%10,%11,%12,%13,%14,%15,%16,%17,%18,%19,%20,%21,%22,%23,%24,%25,%26,%27,%28,%29,%30,%31}, " \
        "da, db, p, 1, 1, 1, 1;\n}"                                                                             \
        : R8(C, d, 0), R8(C, d, 8), R8(C, d, 16), R8(C, d, 24) : "r"(da), "r"(db), "r"(DESC_HI));               \
}
#define DEF_WG_SS16(NAME, C, PRED)                                                                              \
__device__ __forceinline__ void NAME(float (&d)[8], uint32_t da, uint32_t db) {                                 \
    asm volatile("{\n.reg .pred p;\n.reg .b64 da, db;\n" PRED "mov.b64 da, {%8, %10};\nmov.b64 db, {%9, %10};\n"   \
        "wgmma.mma_async.sync.aligned.m64n16k16.f32.bf16.bf16 {%0,%1,%2,%3,%4,%5,%6,%7}, da, db, p, 1, 1, 1, 1;\n}" \
        : R8(C, d, 0) : "r"(da), "r"(db), "r"(DESC_HI));                                                        \
}
#define DEF_WG_SS48(NAME, C, PRED)                                                                              \
__device__ __forceinline__ void NAME(float (&d)[24], uint32_t da, uint32_t db) {                                \
    asm volatile("{\n.reg .pred p;\n.reg .b64 da, db;\n" PRED "mov.b64 da, {%24, %26};\nmov.b64 db, {%25, %26};\n"  \
        "wgmma.mma_async.sync.aligned.m64n48k16.f32.bf16.bf16 "                                                 \
        "{%0,%1,%2,%3,%4,%5,%6,%7,%8,%9,%10,%11,%12,%13,%14,%15,%16,%17,%18,%19,%20,%21,%22,%23}, da, db, p, 1, 1, 1, 1;\n}" \
        : R8(C, d, 0), R8(C, d, 8), R8(C, d, 16) : "r"(da), "r"(db), "r"(DESC_HI));                             \
}
#define DEF_WG_RS16(NAME, C, PRED)                                                                              \
__device__ __forceinline__ void NAME(float (&d)[8], const uint32_t (&a)[4], uint32_t db) {                      \
    asm volatile("{\n.reg .pred p;\n.reg .b64 db;\n" PRED "mov.b64 db, {%12, %13};\n"                           \
        "wgmma.mma_async.sync.aligned.m64n16k16.f32.bf16.bf16 {%0,%1,%2,%3,%4,%5,%6,%7}, {%8,%9,%10,%11}, db, p, 1, 1, 1;\n}" \
        : R8(C, d, 0) : "r"(a[0]), "r"(a[1]), "r"(a[2]), "r"(a[3]), "r"(db), "r"(DESC_HI));                     \
}
#define DEF_WG_RS48(NAME, C, PRED)                                                                              \
__device__ __forceinline__ void NAME(float (&d)[24], const uint32_t (&a)[4], uint32_t db) {                     \
    asm volatile("{\n.reg .pred p;\n.reg .b64 db;\n" PRED "mov.b64 db, {%28, %29};\n"                           \
        "wgmma.mma_async.sync.aligned.m64n48k16.f32.bf16.bf16 "                                                 \
        "{%0,%1,%2,%3,%4,%5,%6,%7,%8,%9,%10,%11,%12,%13,%14,%15,%16,%17,%18,%19,%20,%21,%22,%23}, {%24,%25,%26,%27}, db, p, 1, 1, 1;\n}" \
        : R8(C, d, 0), R8(C, d, 8), R8(C, d, 16) : "r"(a[0]), "r"(a[1]), "r"(a[2]), "r"(a[3]), "r"(db), "r"(DESC_HI)); \
}
#define C_OUT "=f"
#define C_IO "+f"
DEF_WG_SS64(wg_ss64_first, C_OUT, WG_PRED_FIRST)
DEF_WG_SS64(wg_ss64_acc, C_IO, WG_PRED_ACC)
DEF_WG_SS48(wg_ss48_first, C_OUT, WG_PRED_FIRST)
DEF_WG_SS48(wg_ss48_acc, C_IO, WG_PRED_ACC)
DEF_WG_SS16(wg_ss16_first, C_OUT, WG_PRED_FIRST)
DEF_WG_SS16(wg_ss16_acc, C_IO, WG_PRED_ACC)
DEF_WG_RS16(wg_rs16_first, C_OUT, WG_PRED_FIRST)
DEF_WG_RS16(wg_rs16_acc, C_IO, WG_PRED_ACC)
DEF_WG_RS48(wg_rs48_first, C_OUT, WG_PRED_FIRST)
DEF_WG_RS48(wg_rs48_acc, C_IO, WG_PRED_ACC)

__device__ __forceinline__ uint32_t radial2(float d, uint32_t f2) {
    const float scale = edge_fcut(d) * rcp_apx(d);
    const uint32_t a = hmul2_bf(pack_bf2(d, d), f2);
    const float a0 = bf_lo(a), a1 = bf_hi(a);
    if (__builtin_expect(fmaxf(fabsf(a0), fabsf(a1)) > 200.f, 0))
        return pack_bf2(sinf(a0) * scale, sinf(a1) * scale);
    return pack_bf2(__sinf(a0) * scale, __sinf(a1) * scale);
}

__device__ __forceinline__ void load_tile(uint32_t tb, const __nv_bfloat16* sv, int tile, int lane) {
    const char* g = (const char*)(sv + (size_t)tile * 16 * 256) + lane * 16;
    const uint32_t d = tb + lane * 16 + (lane >= 8 ? 128 : 0);
#pragma unroll 4
    for (int r = 0; r < 16; r++) cp_async16(d + r * TILE_STRIDE, g + r * 512);
    asm volatile("cp.async.commit_group;" ::: "memory");
}
__device__ __forceinline__ void build_tile(uint32_t sb, uint32_t tb, int tile, int lane) {
    const int g = lane >> 2, t = lane & 3;
    const int m = lane >> 3, r = lane & 7;
    asm volatile("cp.async.wait_group 0;" ::: "memory");
    __syncwarp();
    float acc[8][4];
#pragma unroll
    for (int i = 0; i < 8; i++) { acc[i][0] = acc[i][1] = acc[i][2] = acc[i][3] = 0.f; }
#pragma unroll 1
    for (int ks = 0; ks < 4; ks++) {
        uint32_t a[4];
        ldsm_x4(a, tb + ((m & 1) * 8 + r) * TILE_STRIDE + (ks * 16 + (m >> 1) * 8) * 2);
#pragma unroll
        for (int np = 0; np < 4; np++) {
            uint32_t b[4];
            ldsm_x4_t(b, sb + SM_W1S + (ks * 16 + (m & 1) * 8 + r) * W1STRIDE + (np * 16 + (m >> 1) * 8) * 2);
            mma16816(acc[2 * np], a, b[0], b[1]);
            mma16816(acc[2 * np + 1], a, b[2], b[3]);
        }
    }
    uint32_t hf[4][4];
#pragma unroll
    for (int i = 0; i < 8; i++) {
        float x[4];
#pragma unroll
        for (int k = 0; k < 4; k++) {
            float v = rbf(acc[i][k]);
            x[k] = __fdividef(v, 1.0f + __expf(-v));
        }
        hf[i >> 1][(i & 1) * 2] = pack_bf2(x[0], x[1]);
        hf[i >> 1][(i & 1) * 2 + 1] = pack_bf2(x[2], x[3]);
    }
    __syncwarp();
    uint32_t ph[8][2];
#pragma unroll 1
    for (int bi = 0; bi < 3; bi++) {
        const int col = bi == 0 ? 128 : bi == 1 ? 0 : 64;
#pragma unroll
        for (int i = 0; i < 8; i++) { acc[i][0] = acc[i][1] = acc[i][2] = acc[i][3] = 0.f; }
#pragma unroll
        for (int ks = 0; ks < 4; ks++) {
#pragma unroll
            for (int np = 0; np < 4; np++) {
                uint32_t b[4];
                ldsm_x4_t(b, sb + SM_W2P + (ks * 16 + (m & 1) * 8 + r) * WSTRIDE + (col + np * 16 + (m >> 1) * 8) * 2);
                mma16816(acc[2 * np], hf[ks], b[0], b[1]);
                mma16816(acc[2 * np + 1], hf[ks], b[2], b[3]);
            }
        }
#pragma unroll
        for (int i = 0; i < 8; i++) { ph[i][0] = pack_bf2(acc[i][0], acc[i][1]); ph[i][1] = pack_bf2(acc[i][2], acc[i][3]); }
        if (bi < 2) {
            const uint32_t dcol = bi == 0 ? 128 : 0;
#pragma unroll
            for (int i = 0; i < 8; i++) {
                sts32(tb + g * TILE_STRIDE + dcol + (i * 8 + 2 * t) * 2, ph[i][0]);
                sts32(tb + (g + 8) * TILE_STRIDE + dcol + (i * 8 + 2 * t) * 2, ph[i][1]);
            }
        }
    }
#pragma unroll 1
    for (int c = 0; c < 3; c++) {
        uint2 v[4][2];
#pragma unroll
        for (int w = 0; w < 4; w++) {
            v[w][0] = lds64(tb + g * TILE_STRIDE + (128 + 64 * c + 16 * w + 4 * t) * 2);
            v[w][1] = lds64(tb + (g + 8) * TILE_STRIDE + (128 + 64 * c + 16 * w + 4 * t) * 2);
        }
        __syncwarp();
#pragma unroll
        for (int w = 0; w < 4; w++) {
#pragma unroll
            for (int hh = 0; hh < 2; hh++) {
                uint32_t ev = __byte_perm(v[w][hh].x, v[w][hh].y, 0x5410);
                uint32_t od = __byte_perm(v[w][hh].x, v[w][hh].y, 0x7632);
                uint32_t rowb = tb + (g + 8 * hh) * TILE_STRIDE + (128 + 64 * c + 16 * w + 2 * t) * 2;
                sts32(rowb, hmul2_bf(ph[2 * w][hh], ev));
                sts32(rowb + 16, hmul2_bf(ph[2 * w + 1][hh], od));
            }
        }
    }
    __syncwarp();
    uint4* gt = reinterpret_cast<uint4*>(g_table + (size_t)tile * 16 * 320);
#pragma unroll 4
    for (int it = 0; it < 20; it++) {
        const int f = it * 32 + lane, row = f / 40, ch = f - row * 40;
        gt[f] = lds128(tb + row * TILE_STRIDE + ch * 16);
    }
    __syncwarp();
}

__device__ __noinline__ void slow_path(const Params& P, uint8_t* smem, int q, int nlocal) {
    float* accX = reinterpret_cast<float*>(smem + 65536);
    float* accU = accX + 4096;
    float* coef = accU + 3072;
    uint2* queue = reinterpret_cast<uint2*>(coef + 64);
    int* misc = reinterpret_cast<int*>(smem + SM_MISC);
    const uint32_t sb = smem_u32(smem);
    const int tid = threadIdx.x;
    for (int nl = 0; nl < nlocal; nl++) {
        const int node = q * P.nper + nl;
        for (int i = tid; i < 4096 + 3072; i += NT) accX[i] = 0.f;
        if (tid == 0) misc[MISC_QN] = 0;
        __syncthreads();
        for (int base = 0; base < EE; base += NT) {
            const int f = base + tid;
            bool hit = false;
            if (f < EE && P.dst[f] == node) {
                const int s = P.src[f];
                uint32_t sxy, sz, dxy, dz;
                load_pos(sb + SM_POS, s, sxy, sz);
                load_pos(sb + SM_POS, node, dxy, dz);
                const uint32_t rxy = hsub2_bf(sxy, dxy), rz = hsub2_bf(sz, dz) & 0xFFFF;
                if (edge_dist(rxy, rz) < 5.0f) {
                    hit = true;
                    int sl = atomicAdd(&misc[MISC_QN], 1);
                    queue[sl] = make_uint2((uint32_t)s | (rxy << 16), (rxy >> 16) | (rz << 16));
                }
            }
            if (!__syncthreads_or(hit)) continue;
            const int qn = misc[MISC_QN];
            for (int k = 0; k < qn; k++) {
                uint2 en = queue[k];
                if (tid < 64) {
                    uint32_t rxy = (en.x >> 16) | (en.y << 16), rz = en.y >> 16;
                    float d = edge_dist(rxy, rz);
                    float inv = 1.0f / d;
                    float f = __bfloat162float(P.freqs[tid & 15]);
                    float cf = rbf(sinf(rbf(d * f)) * (edge_fcut(d) * inv));
                    int c = tid >> 4;
                    float mult = c == 0 ? 1.f : rbf((c == 1 ? bf_lo(rxy) : c == 2 ? bf_hi(rxy) : bf_lo(rz)) * inv);
                    coef[tid] = rbf(cf * mult);
                }
                __syncthreads();
                const unsigned short* row = reinterpret_cast<const unsigned short*>(g_table) + (size_t)(en.x & 0xFFFF) * 320;
                for (int i = tid; i < 4096; i += NT) accX[i] += coef[i >> 6] * bf_lo(__ldcg(row + (i < 1024 ? 0 : 64) + (i & 63)));
                for (int i = tid; i < 3072; i += NT) accU[i] += coef[i / 192] * bf_lo(__ldcg(row + 128 + i % 192));
                __syncthreads();
            }
            if (tid == 0) misc[MISC_QN] = 0;
            __syncthreads();
        }
        if (tid < 256) {
            const int c = tid >> 6, j = tid & 63;
            const int col0 = c == 0 ? 0 : 128;
            const int p = (j & ~15) + 8 * (j & 1) + ((j & 15) >> 1);
            float o = 0.f;
            for (int k = 0; k < 16; k++) {
                o += accX[(c * 16 + k) * 64 + p] * __bfloat162float(P.wr[k * 192 + col0 + j]);
                if (c > 0) o += accU[k * 192 + (c - 1) * 64 + p] * __bfloat162float(P.wr[k * 192 + 64 + j]);
            }
            P.out[(size_t)node * 256 + tid] = __float2bfloat16(o + __bfloat162float(P.sv[(size_t)node * 256 + tid]));
        }
        __syncthreads();
    }
}

__global__ void __launch_bounds__(NT, 1) painn_kernel(const __grid_constant__ Params P) {
    extern __shared__ uint8_t smem_raw[];
    uint8_t* smem = smem_raw + ((1024 - (smem_u32(smem_raw) & 1023)) & 1023);
    const uint32_t sb = smem_u32(smem);
    const int tid = threadIdx.x, lane = tid & 31;
    const int wu = __shfl_sync(0xffffffffu, tid >> 5, 0);
    const int q = blockIdx.x, nP = gridDim.x;
    int* hist = reinterpret_cast<int*>(smem + SM_HIST);
    int* cnt = reinterpret_cast<int*>(smem + SM_CNT);
    int* misc = reinterpret_cast<int*>(smem + SM_MISC);
    uint32_t* glist = reinterpret_cast<uint32_t*>(smem + SM_GL);
    const uint32_t bar_full = sb + SM_BAR, bar_empty = bar_full + 96;
    const uint32_t bar_pos = bar_full + 192, bar_in = bar_full + 200;
    const int nlocal = min(P.nper, NN - q * P.nper);

    STAMP(0, tid == 0);
    int4 s4[4], d4[4];
    if (wu < NEWW) {
        const int i0 = q * P.e4q, i1 = min(i0 + P.e4q, EE / 4);
#pragma unroll
        for (int u = 0; u < 4; u++) {
            int idx = i0 + tid + u * NEW_;
            d4[u] = make_int4(-1, -1, -1, -1); s4[u] = make_int4(0, 0, 0, 0);
            if (idx < i1) {
                d4[u] = ldg_stream(reinterpret_cast<const int4*>(P.dst) + idx);
                s4[u] = ldg_stream(reinterpret_cast<const int4*>(P.src) + idx);
            }
        }
    } else if (tid == NT - 1) {
        for (int i = 0; i < 2 * NSLOT; i++) { mbar_init(bar_full + i * 8, 33); mbar_init(bar_empty + i * 8, 4); }
        mbar_init(bar_pos, 1);
        mbar_init(bar_in, 1);
        misc[MISC_OVF] = 0;
        fence_proxy_async();
        asm volatile("mbarrier.arrive.expect_tx.shared.b64 _, [%0], %1;" :: "r"(bar_pos), "r"(NN * 6) : "memory");
        asm volatile("cp.async.bulk.shared::cluster.global.mbarrier::complete_tx::bytes [%0], [%1], %2, [%3];"
                     :: "r"(sb + SM_POS), "l"(P.pos), "r"(NN * 6), "r"(bar_pos) : "memory");
    }
    unsigned cnt0 = 0;
    if (tid == 0 || tid == NT - 32) cnt0 = ld_relaxed(tid == 0 ? &g_barA : &g_barB);
    if (tid < MAXP) hist[tid] = 1;
    if (tid < 132) cnt[tid] = 0;
    __syncthreads();
    if (wu < NEWW) {
        STAMP(6, tid == 0);
        mbar_wait(bar_pos, 0);
        STAMP(13, tid == 0);
#pragma unroll 1
        for (int u = 0; u < 2; u++) {
            const int dd[8] = {d4[0].x, d4[0].y, d4[0].z, d4[0].w, d4[1].x, d4[1].y, d4[1].z, d4[1].w};
            const int ss[8] = {s4[0].x, s4[0].y, s4[0].z, s4[0].w, s4[1].x, s4[1].y, s4[1].z, s4[1].w};
            bool ok[8];
#pragma unroll
            for (int k = 0; k < 8; k++) {
                uint32_t sxy, sz, dxy, dz;
                load_pos(sb + SM_POS, ss[k], sxy, sz);
                load_pos(sb + SM_POS, max(dd[k], 0), dxy, dz);
                const uint32_t rxy = hsub2_bf(sxy, dxy), rz = hsub2_bf(sz, dz);
                const uint32_t sq = hmul2_bf(rxy, rxy), sqz = hmul2_bf(rz, rz);
                ok[k] = dd[k] >= 0 && rbf((bf_lo(sq) + bf_hi(sq)) + bf_lo(sqz)) <= 24.75f;
            }
            uint32_t own[8], slot[8];
#pragma unroll
            for (int k = 0; k < 8; k++) {
                own[k] = __umulhi((uint32_t)max(dd[k], 0), P.magic);
                slot[k] = ok[k] ? atomicAdd(&hist[own[k]], 1) : CAPR;
            }
#pragma unroll
            for (int k = 0; k < 8; k++)
                if (slot[k] < CAPR) sts32(sb + SM_RUNS + own[k] * RUNB + slot[k] * 4, (uint32_t)ss[k] | ((dd[k] - own[k] * P.nper) << 16));
            STAMP(14, tid == 0 && u == 0);
            d4[0] = d4[2]; d4[1] = d4[3]; s4[0] = s4[2]; s4[1] = s4[3];
        }
        bar_sync<4, NEW_>();
        STAMP(2, tid == 0);
        {
            const int nch = nP * (RUNB / 16);
#pragma unroll
            for (int k = 0; k < (MAXP * (RUNB / 16) + NEW_ - 1) / NEW_; k++) {
                const int f = tid + k * NEW_;
                if (f < nch) {
                    const int r = f / (RUNB / 16), ch = f - r * (RUNB / 16);
                    uint4 v = lds128(sb + SM_RUNS + f * 16);
                    if (ch == 0) v.x = hist[r] - 1;
                    reinterpret_cast<uint4*>(g_stage + ((size_t)r * nP + q) * CAPR)[ch] = v;
                }
            }
        }
        bar_sync<4, NEW_>();
        STAMP(3, tid == 0);
        if (tid == 0) red_add_release(&g_barA, 1);
        bar_sync<4, NEW_>();
        if (tid >= 32) {
            if (tid - 32 < nlocal) {
                uint32_t xy, z;
                load_pos(sb + SM_POS, q * P.nper + tid - 32, xy, z);
                sts64(sb + SM_GL + (tid - 32) * 8, xy, z);
            }
            const uint32_t f2 = __ldg(reinterpret_cast<const uint32_t*>(P.freqs) + (tid & 7));
#pragma unroll 2
            for (int i = tid - 32; i < LUT_N * 8; i += NEW_ - 32)
                sts32(sb + SM_LUT + i * 4, radial2(__uint_as_float((uint32_t)(LUT_BASE + (i >> 3)) << 16), f2));
        }
        if (tid == 0) {
            STAMP(15, true);
            wait_counter(&g_barA, (cnt0 / (unsigned)nP + 1) * (unsigned)nP);
            asm volatile("fence.proxy.async;" ::: "memory");
            asm volatile("mbarrier.arrive.expect_tx.shared.b64 _, [%0], %1;" :: "r"(bar_in), "r"(nP * RUNB) : "memory");
            asm volatile("cp.async.bulk.shared::cluster.global.mbarrier::complete_tx::bytes [%0], [%1], %2, [%3];"
                         :: "r"(sb + SM_RUNS), "l"(g_stage + (size_t)q * nP * CAPR), "r"(nP * RUNB), "r"(bar_in) : "memory");
        }
        STAMP(5, tid == 0);
    } else {
        const int tw = wu - NEWW, tt = tid - NEW_;
        for (int i = tt; i < 512; i += 160)
            cp_async16(sb + SM_W1S + (i >> 3) * W1STRIDE + (i & 7) * 16, reinterpret_cast<const char*>(P.w1) + i * 16);
        asm volatile("cp.async.commit_group;" ::: "memory");
#pragma unroll 1
        for (int u0 = 0; u0 < 6; u0 += 3) {
            uint4 x[3][2];
#pragma unroll
            for (int u = 0; u < 3; u++) {
                const int item = tt + (u0 + u) * 160;
                const __nv_bfloat16* g = item < 768 ? P.w2 + item * 16 : P.wr + (item - 768) * 16;
                x[u][0] = __ldg(reinterpret_cast<const uint4*>(g));
                x[u][1] = __ldg(reinterpret_cast<const uint4*>(g) + 1);
            }
            if (u0 == 3) {
                if (q + nP * tw < NTILES) load_tile(sb + SM_TILE + tw * TILE_BYTES, P.sv, q + nP * tw, lane);
            }
#pragma unroll
            for (int u = 0; u < 3; u++) {
                const int item = tt + (u0 + u) * 160;
                const int row = item / 12, blk = item - row * 12;
                const uint32_t a = sb + SM_W2P + row * WSTRIDE + blk * 32;
                uint4 ev, od;
                ev.x = __byte_perm(x[u][0].x, x[u][0].y, 0x5410); od.x = __byte_perm(x[u][0].x, x[u][0].y, 0x7632);
                ev.y = __byte_perm(x[u][0].z, x[u][0].w, 0x5410); od.y = __byte_perm(x[u][0].z, x[u][0].w, 0x7632);
                ev.z = __byte_perm(x[u][1].x, x[u][1].y, 0x5410); od.z = __byte_perm(x[u][1].x, x[u][1].y, 0x7632);
                ev.w = __byte_perm(x[u][1].z, x[u][1].w, 0x5410); od.w = __byte_perm(x[u][1].z, x[u][1].w, 0x7632);
                sts128(a, ev); sts128(a + 16, od);
            }
        }
        asm volatile("cp.async.wait_group 1;" ::: "memory");
        bar_sync<5, 160>();
        STAMP(1, tt == 0);
#pragma unroll 1
        for (int tile = q + nP * tw; tile < NTILES; tile += nP * NTILEW) {
            build_tile(sb, sb + SM_TILE + tw * TILE_BYTES, tile, lane);
            if (lane == 0) red_add_release(&g_barB, 1);
            if (tile + nP * NTILEW < NTILES) load_tile(sb + SM_TILE + tw * TILE_BYTES, P.sv, tile + nP * NTILEW, lane);
        }
        STAMP(4, tt == 0);
    }
    __syncthreads();
    mbar_wait(bar_pos, 0);
    mbar_wait(bar_in, 0);
    STAMP(7, tid == 0);
    if (wu < 15) {
        bool ovf = false;
#pragma unroll 1
        for (int r0 = wu; r0 < nP; r0 += 15 * 9) {
            uint32_t e[9], rxy[9], rz[9];
            int n[9], slot[9];
            int nmax = 0;
#pragma unroll
            for (int u = 0; u < 9; u++) {
                const int r = min(r0 + 15 * u, nP - 1);
                n[u] = r0 + 15 * u < nP ? (int)lds32(sb + SM_RUNS + r * RUNB) : 0;
                e[u] = lds32(sb + SM_RUNS + r * RUNB + (1 + lane) * 4);
            }
#pragma unroll
            for (int u = 0; u < 9; u++) {
                nmax = max(nmax, n[u]);
                if (lane >= n[u]) e[u] = 0;
                uint32_t sxy, sz;
                load_pos(sb + SM_POS, e[u] & 0xFFFF, sxy, sz);
                const uint2 dp = lds64(sb + SM_GL + (e[u] >> 16) * 8);
                rxy[u] = hsub2_bf(sxy, dp.x); rz[u] = hsub2_bf(sz, dp.y);
            }
#pragma unroll
            for (int u = 0; u < 9; u++) slot[u] = lane < n[u] ? atomicAdd(&cnt[e[u] >> 16], 1) : 0;
#pragma unroll
            for (int u = 0; u < 9; u++) {
                if (lane < n[u]) {
                    if (slot[u] < P.capn)
                        sts64(sb + SM_BKT + ((e[u] >> 16) * P.capn + slot[u]) * 8, (e[u] & 0xFFFF) | (rxy[u] << 16), (rxy[u] >> 16) | (rz[u] << 16));
                    else ovf = true;
                }
            }
            ovf |= nmax >= CAPR;
            if (nmax > 32) {
#pragma unroll 1
                for (int u = 0; u < 9; u++) {
                    const int r = r0 + 15 * u;
                    if (r >= nP) break;
                    const int nn = min((int)lds32(sb + SM_RUNS + r * RUNB), CAPR - 1);
                    for (int i = 33 + lane; i <= nn; i += 32) {
                        const uint32_t ee = lds32(sb + SM_RUNS + r * RUNB + i * 4);
                        uint32_t sxy, sz;
                        load_pos(sb + SM_POS, ee & 0xFFFF, sxy, sz);
                        const uint2 dp = lds64(sb + SM_GL + (ee >> 16) * 8);
                        const uint32_t axy = hsub2_bf(sxy, dp.x), az = hsub2_bf(sz, dp.y);
                        const int sl = atomicAdd(&cnt[ee >> 16], 1);
                        if (sl < P.capn) sts64(sb + SM_BKT + ((ee >> 16) * P.capn + sl) * 8, (ee & 0xFFFF) | (axy << 16), (axy >> 16) | (az << 16));
                        else ovf = true;
                    }
                }
            }
        }
        if (ovf) misc[MISC_OVF] = 1;
    } else if (lane == 0) {
        wait_counter(&g_barB, (cnt0 / (unsigned)NTILES + 1) * (unsigned)NTILES);
    }
    __syncthreads();
    STAMP(8, tid == 0);
    if (misc[MISC_OVF]) {
        slow_path(P, smem, q, nlocal);
        return;
    }
    {
        int c = 0, G = 0, inc = 0;
        if (wu < 4) {
            c = tid < nlocal ? cnt[tid] : 0;
            G = tid < nlocal ? max(1, (c + 15) >> 4) : 0;
            inc = G;
#pragma unroll
            for (int o = 1; o < 32; o <<= 1) { int y = __shfl_up_sync(0xffffffffu, inc, o); if (lane >= o) inc += y; }
            if (lane == 31) misc[MISC_WT2 + wu] = inc;
        }
        __syncthreads();
        if (wu < 4) {
            int w0 = misc[MISC_WT2], w1 = misc[MISC_WT2 + 1], w2 = misc[MISC_WT2 + 2], w3 = misc[MISC_WT2 + 3];
            int gtot = w0 + w1 + w2 + w3;
            int gpre = inc - G + (wu > 0 ? w0 : 0) + (wu > 1 ? w1 : 0) + (wu > 2 ? w2 : 0);
            for (int g = 0; g < G; g++)
                glist[gpre + g] = (uint32_t)(tid * P.capn + 16 * g) | ((uint32_t)min(16, c - 16 * g) << 16);
            int half = gtot >> 1;
            if (G > 0 && gpre <= half && half < gpre + G) {
                const bool before = half - gpre <= gpre + G - half;
                misc[MISC_GSPLIT] = before ? gpre : gpre + G;
                misc[MISC_NSPLIT] = before ? tid : tid + 1;
            }
            if (tid == 0) misc[MISC_GTOT] = gtot;
            cnt[tid] = G;
        }
        __syncthreads();
    }
    STAMP(9, tid == 0);

    const int gsplit = misc[MISC_GSPLIT], gtot = misc[MISC_GTOT], nsplit = misc[MISC_NSPLIT];
    const int g = lane >> 2, t = lane & 3, m = lane >> 3, r = lane & 7;
    const bool tb0 = t & 1, tb1 = t & 2;
#define FENCE_REGS8(x, o) asm volatile("" : "+f"(x[o]), "+f"(x[o + 1]), "+f"(x[o + 2]), "+f"(x[o + 3]), "+f"(x[o + 4]), "+f"(x[o + 5]), "+f"(x[o + 6]), "+f"(x[o + 7]) :: "memory")
#define QUAD_REDUCE(v, o0, o1)                                                                          \
    {                                                                                                   \
        float k4[4];                                                                                    \
        _Pragma("unroll")                                                                               \
        for (int i = 0; i < 4; i++)                                                                     \
            k4[i] = (tb0 ? v[4 + i] : v[i]) + __shfl_xor_sync(0xffffffffu, tb0 ? v[i] : v[4 + i], 1);   \
        o0 = (tb1 ? k4[2] : k4[0]) + __shfl_xor_sync(0xffffffffu, tb1 ? k4[0] : k4[2], 2);              \
        o1 = (tb1 ? k4[3] : k4[1]) + __shfl_xor_sync(0xffffffffu, tb1 ? k4[1] : k4[3], 2);              \
    }
    if (wu >= 8) {
        if (wu >= 14) return;
        const int team = wu >= 11 ? 1 : 0, pw = wu - 8 - 3 * team;
        const int gbeg = team == 0 ? 0 : gsplit, gcount = (team == 0 ? gsplit : gtot) - gbeg;
        const int e = lane & 15, hb = lane >> 4;
        const char* lane_src = reinterpret_cast<const char*>(g_table) + lane * 16;
        const char* lane_src5 = reinterpret_cast<const char*>(g_table) + 512 + (lane & 7) * 16;
        asm volatile("" : "+l"(lane_src), "+l"(lane_src5));
        const int s0 = team * NSLOT + pw * 2;
        const uint32_t x7 = (lane & 7) << 4;
        const uint32_t rowb = sb + SM_RING + s0 * SLOTB + (lane >> 3) * 2048;
        const uint32_t row5 = sb + SM_RING + s0 * SLOTB + 4 * 2048 + (lane >> 3) * 128;
        const uint32_t x5a = x7 ^ ((lane >> 3) << 4), x5b = x7 ^ (((lane >> 3) + 4) << 4);
        const uint32_t cb = sb + SM_COEF + (s0 + hb) * 2048 + e * 128;
        const uint32_t cx = (e & 7) << 4;
        const uint32_t csr_lane = sb + SM_BKT + e * 8;
        const uint32_t fullA = bar_full + s0 * 8, emptyA = bar_empty + s0 * 8;
        bar_sync<3, 448>();
        uint32_t par = 1;
        for (int gA = 2 * pw; gA < gcount; gA += NSLOT) {
            const bool hasB = gA + 1 < gcount;
            uint32_t info = 0;
            if (gA + hb < gcount) info = glist[gbeg + gA + hb];
            const bool valid = e < (int)(info >> 16);
            uint2 en = make_uint2(0u, 0u);
            if (valid) en = lds64(csr_lane + (info & 0xFFFF) * 8);
            const uint32_t rxy = (en.x >> 16) | (en.y << 16), rz = en.y >> 16;
            const float d = edge_dist(rxy, rz);
            uint4 ca = make_uint4(0u, 0u, 0u, 0u), cb4 = ca;
            const int li = (int)(__float_as_uint(d) >> 16) - LUT_BASE;
            if (valid && li >= 0) { ca = lds128(sb + SM_LUT + li * 32); cb4 = lds128(sb + SM_LUT + li * 32 + 16); }
            if (__any_sync(0xffffffffu, valid && li < 0)) {
                if (valid && li < 0) {
                    const uint32_t* fp = reinterpret_cast<const uint32_t*>(P.freqs);
                    uint32_t o[8];
#pragma unroll 1
                    for (int p = 0; p < 8; p++) {
                        const uint32_t c2 = radial2(d, __ldg(fp + p));
#pragma unroll
                        for (int x = 0; x < 7; x++) o[x] = o[x + 1];
                        o[7] = c2;
                    }
                    ca = make_uint4(o[0], o[1], o[2], o[3]); cb4 = make_uint4(o[4], o[5], o[6], o[7]);
                }
            }
            const float inv = rcp_apx(d);
            const float hx = bf_lo(rxy) * inv, hy = bf_hi(rxy) * inv, hz = bf_lo(rz) * inv;
            const uint32_t hx2 = pack_bf2(hx, hx), hy2 = pack_bf2(hy, hy), hz2 = pack_bf2(hz, hz);
            const uint32_t srcn = valid ? (en.x & 0xFFFF) : 0xFFFFFFFFu;
            const unsigned vmask = __ballot_sync(0xffffffffu, valid);
#pragma unroll
            for (int hh = 0; hh < 2; hh++) {
                if (hh == 1 && !hasB) break;
                if (team == 0) TRACE(gA + hh, 0);
                mbar_wait(emptyA + hh * 8, par);
                if (team == 0) TRACE(gA + hh, 1);
                const unsigned gm = (vmask >> (16 * hh)) & 0xFFFFu;
                if (gm == 0xFFFFu) {
#pragma unroll
                    for (int rr = 0; rr < 16; rr++) {
                        const uint32_t s = __shfl_sync(0xffffffffu, srcn, 16 * hh + rr);
                        cp_async16(rowb + hh * SLOTB + rr * 128 + (x7 ^ ((rr & 7) << 4)), lane_src + (size_t)s * ROWB);
                    }
#pragma unroll
                    for (int j = 0; j < 4; j++) {
                        const uint32_t s = __shfl_sync(0xffffffffu, srcn, 16 * hh + 4 * j + (lane >> 3));
                        cp_async16(row5 + hh * SLOTB + j * 512 + ((j & 1) ? x5b : x5a), lane_src5 + (size_t)s * ROWB);
                    }
                } else if (gA >= NSLOT) {
#pragma unroll
                    for (int rr = 0; rr < 16; rr++) {
                        const uint32_t s = __shfl_sync(0xffffffffu, srcn, 16 * hh + rr);
                        cp_async16_valid(rowb + hh * SLOTB + rr * 128 + (x7 ^ ((rr & 7) << 4)), lane_src + (size_t)s * ROWB, s);
                    }
#pragma unroll
                    for (int j = 0; j < 4; j++) {
                        const uint32_t s = __shfl_sync(0xffffffffu, srcn, 16 * hh + 4 * j + (lane >> 3));
                        cp_async16_valid(row5 + hh * SLOTB + j * 512 + ((j & 1) ? x5b : x5a), lane_src5 + (size_t)s * ROWB, s);
                    }
                } else {
#pragma unroll 1
                    for (int rr = 0; rr < 16; rr++) {
                        const uint32_t s = __shfl_sync(0xffffffffu, srcn, 16 * hh + rr);
                        const bool ok = s != 0xFFFFFFFFu;
                        cp_async16_zfill(rowb + hh * SLOTB + rr * 128 + (x7 ^ ((rr & 7) << 4)), lane_src + (size_t)(ok ? s : 0u) * ROWB, ok ? 16 : 0);
                    }
#pragma unroll 1
                    for (int j = 0; j < 4; j++) {
                        const uint32_t s = __shfl_sync(0xffffffffu, srcn, 16 * hh + 4 * j + (lane >> 3));
                        const bool ok = s != 0xFFFFFFFFu;
                        cp_async16_zfill(row5 + hh * SLOTB + j * 512 + ((j & 1) ? x5b : x5a), lane_src5 + (size_t)(ok ? s : 0u) * ROWB, ok ? 16 : 0);
                    }
                }
                cp_async_arrive_noinc(fullA + hh * 8);
                if (team == 0) TRACE(gA + hh, 2);
            }
            if (hb == 0 || hasB) {
                sts128(cb + cx, ca);
                sts128(cb + (cx ^ 0x10), cb4);
                sts128(cb + (cx ^ 0x20), make_uint4(hmul2_bf(ca.x, hx2), hmul2_bf(ca.y, hx2), hmul2_bf(ca.z, hx2), hmul2_bf(ca.w, hx2)));
                sts128(cb + (cx ^ 0x30), make_uint4(hmul2_bf(cb4.x, hx2), hmul2_bf(cb4.y, hx2), hmul2_bf(cb4.z, hx2), hmul2_bf(cb4.w, hx2)));
                sts128(cb + (cx ^ 0x40), make_uint4(hmul2_bf(ca.x, hy2), hmul2_bf(ca.y, hy2), hmul2_bf(ca.z, hy2), hmul2_bf(ca.w, hy2)));
                sts128(cb + (cx ^ 0x50), make_uint4(hmul2_bf(cb4.x, hy2), hmul2_bf(cb4.y, hy2), hmul2_bf(cb4.z, hy2), hmul2_bf(cb4.w, hy2)));
                sts128(cb + (cx ^ 0x60), make_uint4(hmul2_bf(ca.x, hz2), hmul2_bf(ca.y, hz2), hmul2_bf(ca.z, hz2), hmul2_bf(ca.w, hz2)));
                sts128(cb + (cx ^ 0x70), make_uint4(hmul2_bf(cb4.x, hz2), hmul2_bf(cb4.y, hz2), hmul2_bf(cb4.z, hz2), hmul2_bf(cb4.w, hz2)));
            }
            fence_proxy_async();
            __syncwarp();
            mbar_arrive_elect(fullA);
            if (hasB) mbar_arrive_elect(fullA + 8);
            par ^= 1;
        }
        STAMP(10, wu == 8 && lane == 0);
    } else {
        const int team = wu >> 2, w = wu & 3;
        int node = team == 0 ? 0 : nsplit;
        const int nend = team == 0 ? nsplit : nlocal;
        float xs[8], xu[8], xv[8];
        {
            uint32_t a[4], b[4], c[4];
            ldsm_x4_t(a, sb + SM_WRP + ((m >> 1) * 8 + r) * WSTRIDE + (w * 16 + (m & 1) * 8) * 2);
            ldsm_x4_t(b, sb + SM_WRP + ((m >> 1) * 8 + r) * WSTRIDE + (64 + w * 16 + (m & 1) * 8) * 2);
            ldsm_x4_t(c, sb + SM_WRP + ((m >> 1) * 8 + r) * WSTRIDE + (128 + w * 16 + (m & 1) * 8) * 2);
            bar_arrive<3, 448>();
#pragma unroll
            for (int i = 0; i < 4; i++) {
                xs[2 * i] = bf_lo(a[i]); xs[2 * i + 1] = bf_hi(a[i]);
                xu[2 * i] = bf_lo(b[i]); xu[2 * i + 1] = bf_hi(b[i]);
                xv[2 * i] = bf_lo(c[i]); xv[2 * i + 1] = bf_hi(c[i]);
            }
        }
        const uint32_t drows = desc_lo(sb + SM_RING + team * NSLOT * SLOTB);
        const uint32_t dcoef = desc_lo(sb + SM_COEF + team * NSLOT * 2048);
        const int cc = 2 * (t & 1) + (t >> 1);
        const size_t io0 = ((size_t)q * P.nper + node) * 128 + cc * 32 + w * 8 + g;
        const uint32_t* resp = reinterpret_cast<const uint32_t*>(P.sv) + io0;
        uint32_t* outp = reinterpret_cast<uint32_t*>(P.out) + io0;
        const uint32_t fullb = bar_full + team * NSLOT * 8, emptyb = bar_empty + team * NSLOT * 8;
        uint32_t sl = 0, ph = 0;
        int gtr = 0; (void)gtr;
#define G1_STEP(W48, W16)                                                                               \
        {                                                                                               \
            if (wu == 0) TRACE(gtr, 3);                                                                 \
            CWAIT(fullb + sl * 8, ph);                                                                  \
            if (wu == 0) TRACE(gtr, 4);                                                                 \
            gtr++;                                                                                      \
            const uint32_t dr = drows + sl * (SLOTB / 16), dc = dcoef + sl * 128;                       \
            wg_fence();                                                                                 \
            W48(dv, dr + 128, dc + 2);                                                                  \
            W16(ds, dr, dc);                                                                            \
            W16(u0, dr + 256, dc);                                                                      \
            W16(u1, dr + 384, dc);                                                                      \
            W16(u2, dr + 512, dc);                                                                      \
            wg_commit();                                                                                \
        }
        for (; node < nend; node++) {
            const int G = __shfl_sync(0xffffffffu, cnt[node], 0);
            const uint32_t res = __ldg(resp);
            float ds[8], dv[24], u0[8], u1[8], u2[8];
            G1_STEP(wg_ss48_first, wg_ss16_first)
            uint32_t last = sl;
            sl = sl == NSLOT - 1 ? 0 : sl + 1; ph ^= (sl == 0 ? 1u : 0u);
            for (int gi = 1; gi < G; gi++) {
                G1_STEP(wg_ss48_acc, wg_ss16_acc)
                wg_wait<1>();
                mbar_arrive_elect(emptyb + last * 8);
                last = sl;
                sl = sl == NSLOT - 1 ? 0 : sl + 1; ph ^= (sl == 0 ? 1u : 0u);
            }
            wg_wait<0>();
            mbar_arrive_elect(emptyb + last * 8);
            FENCE_REGS8(ds, 0); FENCE_REGS8(dv, 0); FENCE_REGS8(dv, 8); FENCE_REGS8(dv, 16);
            FENCE_REGS8(u0, 0); FENCE_REGS8(u1, 0); FENCE_REGS8(u2, 0);
            float v[8];
            v[0] = ds[0] * xs[0] + ds[1] * xs[1] + ds[4] * xs[4] + ds[5] * xs[5];
            v[1] = ds[2] * xs[2] + ds[3] * xs[3] + ds[6] * xs[6] + ds[7] * xs[7];
#define VPART(c, U)                                                                                     \
            v[2 + 2 * c] = dv[8 * c] * xv[0] + dv[8 * c + 1] * xv[1] + dv[8 * c + 4] * xv[4] + dv[8 * c + 5] * xv[5] \
                         + U[0] * xu[0] + U[1] * xu[1] + U[4] * xu[4] + U[5] * xu[5];                   \
            v[3 + 2 * c] = dv[8 * c + 2] * xv[2] + dv[8 * c + 3] * xv[3] + dv[8 * c + 6] * xv[6] + dv[8 * c + 7] * xv[7] \
                         + U[2] * xu[2] + U[3] * xu[3] + U[6] * xu[6] + U[7] * xu[7];
            VPART(0, u0) VPART(1, u1) VPART(2, u2)
#undef VPART
            float o0, o1;
            QUAD_REDUCE(v, o0, o1)
            *outp = pack_bf2(o0 + bf_lo(res), o1 + bf_hi(res));
            outp += 128; resp += 128;
            if (wu == 0) TRACE(gtr - 1, 5);
            STAMP(11, wu == 0 && lane == 0); STAMP(12, wu == 4 && lane == 0);
        }
#undef G1_STEP
    }
#undef QUAD_REDUCE
#undef FENCE_REGS8
}

}

extern "C" void kernel_launch(void* const* d_in, const int* in_sizes, int n_in, void* d_out, int out_size) {
    (void)in_sizes; (void)n_in; (void)out_size;
    static int nP = 0;
    if (nP == 0) {
        int dev = 0, sms = 0;
        cudaGetDevice(&dev);
        cudaDeviceGetAttribute(&sms, cudaDevAttrMultiProcessorCount, dev);
        nP = sms < MAXP ? sms : MAXP;
        cudaFuncSetAttribute(painn_kernel, cudaFuncAttributeMaxDynamicSharedMemorySize, SM_ALLOC);
    }
    Params P;
    P.sv = (const __nv_bfloat16*)d_in[0];
    P.pos = (const __nv_bfloat16*)d_in[1];
    P.src = (const int*)d_in[2];
    P.dst = (const int*)d_in[3];
    P.freqs = (const __nv_bfloat16*)d_in[4];
    P.w1 = (const __nv_bfloat16*)d_in[5];
    P.w2 = (const __nv_bfloat16*)d_in[6];
    P.wr = (const __nv_bfloat16*)d_in[7];
    P.out = (__nv_bfloat16*)d_out;
    P.nper = (NN + nP - 1) / nP;
    P.magic = (unsigned)(((1ull << 32) + P.nper - 1) / P.nper);
    P.e4q = (EE / 4 + nP - 1) / nP;
    P.capn = (BKT_ENTRIES / P.nper) & ~15;
    if (P.capn > 96) P.capn = 96;
    cudaLaunchConfig_t cfg = {};
    cfg.gridDim = dim3(nP);
    cfg.blockDim = dim3(NT);
    cfg.dynamicSmemBytes = SM_ALLOC;
    cfg.stream = cudaStreamPerThread;
    cudaLaunchAttribute attr[1];
    attr[0].id = cudaLaunchAttributeCooperative;
    attr[0].val.cooperative = 1;
    cfg.attrs = attr;
    cfg.numAttrs = 1;
    cudaLaunchKernelEx(&cfg, painn_kernel, P);
}
```

```cpp
#include <cuda_runtime.h>
#include <cuda_bf16.h>
#include <stdint.h>

namespace {

constexpr int NN = 10000;
constexpr int EE = 640000;
constexpr int NT = 512;
constexpr int NEWW = 11;
constexpr int NEW_ = NEWW * 32;
constexpr int MAXP = 160;
constexpr int CAPR = 72;
constexpr int RUNB = CAPR * 4;
constexpr int NTILES = NN / 16;
constexpr int NTILEW = 5;
constexpr int BKT_ENTRIES = 7296;

constexpr int NSLOT     = 6;
constexpr int ROWB      = 640;
constexpr int SLOTB     = 5 * 2048;
constexpr int SM_RING   = 0;
constexpr int SM_COEF   = 2 * NSLOT * SLOTB;
constexpr int SM_BKT    = SM_COEF + 2 * NSLOT * 2048;
constexpr int LUT_BASE = 0x3E80, LUT_N = 0x40A0 - 0x3E80;
constexpr int SM_LUT    = SM_BKT + BKT_ENTRIES * 8;
constexpr int SM_GL     = SM_LUT + LUT_N * 32;
constexpr int SM_HIST   = SM_GL + 2048;
constexpr int SM_CNT    = SM_HIST + 640;
constexpr int SM_MISC   = SM_CNT + 528;
constexpr int SM_BAR    = SM_MISC + 128;
constexpr int SM_TOTAL  = SM_BAR + 26 * 8;
constexpr int SM_ALLOC  = SM_TOTAL + 1024;
constexpr int SM_POS    = 0;
constexpr int SM_RUNS   = 60032;
constexpr int SM_W2P    = SM_RUNS + MAXP * RUNB;
constexpr int WSTRIDE   = 400;
constexpr int SM_WRP    = SM_W2P + 64 * WSTRIDE;
constexpr int SM_W1S    = SM_WRP + 16 * WSTRIDE;
constexpr int W1STRIDE  = 144;
constexpr int SM_TILE   = SM_BKT;
constexpr int TILE_STRIDE = 656;
constexpr int TILE_BYTES  = 16 * TILE_STRIDE;
static_assert(SM_ALLOC <= 232448, "smem");
static_assert(NTILEW * TILE_BYTES <= BKT_ENTRIES * 8, "tiles");
static_assert(SM_W1S + 64 * W1STRIDE <= SM_BKT, "weights");

constexpr int MISC_GSPLIT = 9;
constexpr int MISC_GTOT = 10;
constexpr int MISC_NSPLIT = 11;
constexpr int MISC_WT2 = 12;
constexpr int MISC_QN = 16;
constexpr int MISC_OVF = 17;
constexpr int MISC_ROVF = 18;

constexpr int SPIN_LIMIT = 1 << 22;

__device__ __align__(1024) __nv_bfloat16 g_table[NN * 320];
__device__ __align__(128) uint32_t g_stage[MAXP * MAXP * CAPR];
__device__ unsigned g_barA;
__device__ unsigned g_barB;

struct Params {
    const __nv_bfloat16* sv;
    const __nv_bfloat16* pos;
    const int* src;
    const int* dst;
    const __nv_bfloat16* freqs;
    const __nv_bfloat16* w1;
    const __nv_bfloat16* w2;
    const __nv_bfloat16* wr;
    __nv_bfloat16* out;
    int nper;
    unsigned magic;
    int e4q;
    int capn;
    int mode;
};

__device__ __forceinline__ uint32_t smem_u32(const void* p) { return (uint32_t)__cvta_generic_to_shared(p); }
__device__ __forceinline__ void mbar_init(uint32_t bar, uint32_t cnt) {
    asm volatile("mbarrier.init.shared.b64 [%0], %1;" :: "r"(bar), "r"(cnt) : "memory");
}
__device__ __forceinline__ void mbar_arrive_elect(uint32_t bar) {
    asm volatile("{\n.reg .pred p;\nelect.sync _|p, 0xffffffff;\n@p mbarrier.arrive.shared.b64 _, [%0];\n}" :: "r"(bar) : "memory");
}
__device__ __forceinline__ bool mbar_try(uint32_t bar, uint32_t parity) {
    uint32_t ok;
    asm volatile("{\n.reg .pred p;\nmbarrier.try_wait.parity.shared.b64 p, [%1], %2;\nselp.u32 %0, 1, 0, p;\n}"
                 : "=r"(ok) : "r"(bar), "r"(parity) : "memory");
    return ok != 0;
}
__device__ __forceinline__ void mbar_wait(uint32_t bar, uint32_t parity) {
    int it = 0;
    while (!mbar_try(bar, parity)) { if (++it > SPIN_LIMIT) __trap(); }
}
__device__ __forceinline__ void cp_async16(uint32_t dst, const void* src) {
    asm volatile("cp.async.cg.shared.global [%0], [%1], 16;" :: "r"(dst), "l"(src) : "memory");
}
__device__ __forceinline__ void cp_async16_zfill(uint32_t dst, const void* src, int sz) {
    asm volatile("cp.async.cg.shared.global [%0], [%1], 16, %2;" :: "r"(dst), "l"(src), "r"(sz) : "memory");
}
__device__ __forceinline__ void cp_async16_valid(uint32_t dst, const void* src, uint32_t s) {
    asm volatile("{\n.reg .pred p;\nsetp.ne.u32 p, %2, 0xffffffff;\n@p cp.async.cg.shared.global [%0], [%1], 16;\n}"
                 :: "r"(dst), "l"(src), "r"(s) : "memory");
}
__device__ __forceinline__ void cp_async_arrive_noinc(uint32_t bar) {
    asm volatile("cp.async.mbarrier.arrive.noinc.shared.b64 [%0];" :: "r"(bar) : "memory");
}
__device__ __forceinline__ void fence_proxy_async() { asm volatile("fence.proxy.async.shared::cta;" ::: "memory"); }
__device__ __forceinline__ void ldsm_x4(uint32_t (&r)[4], uint32_t addr) {
    asm volatile("ldmatrix.sync.aligned.m8n8.x4.shared.b16 {%0,%1,%2,%3}, [%4];"
                 : "=r"(r[0]), "=r"(r[1]), "=r"(r[2]), "=r"(r[3]) : "r"(addr) : "memory");
}
__device__ __forceinline__ void ldsm_x4_t(uint32_t (&r)[4], uint32_t addr) {
    asm volatile("ldmatrix.sync.aligned.m8n8.x4.trans.shared.b16 {%0,%1,%2,%3}, [%4];"
                 : "=r"(r[0]), "=r"(r[1]), "=r"(r[2]), "=r"(r[3]) : "r"(addr) : "memory");
}
__device__ __forceinline__ void mma16816(float (&c)[4], const uint32_t (&a)[4], uint32_t b0, uint32_t b1) {
    asm volatile("mma.sync.aligned.m16n8k16.row.col.f32.bf16.bf16.f32 {%0,%1,%2,%3}, {%4,%5,%6,%7}, {%8,%9}, {%0,%1,%2,%3};"
                 : "+f"(c[0]), "+f"(c[1]), "+f"(c[2]), "+f"(c[3])
                 : "r"(a[0]), "r"(a[1]), "r"(a[2]), "r"(a[3]), "r"(b0), "r"(b1));
}
__device__ __forceinline__ uint32_t lds32(uint32_t a) { uint32_t v; asm volatile("ld.shared.u32 %0, [%1];" : "=r"(v) : "r"(a) : "memory"); return v; }
__device__ __forceinline__ uint2 lds64(uint32_t a) { uint2 v; asm volatile("ld.shared.v2.u32 {%0,%1}, [%2];" : "=r"(v.x), "=r"(v.y) : "r"(a) : "memory"); return v; }
__device__ __forceinline__ uint4 lds128(uint32_t a) { uint4 v; asm volatile("ld.shared.v4.u32 {%0,%1,%2,%3}, [%4];" : "=r"(v.x), "=r"(v.y), "=r"(v.z), "=r"(v.w) : "r"(a) : "memory"); return v; }
__device__ __forceinline__ void sts32(uint32_t a, uint32_t v) { asm volatile("st.shared.u32 [%0], %1;" :: "r"(a), "r"(v) : "memory"); }
__device__ __forceinline__ void sts64(uint32_t a, uint32_t x, uint32_t y) { asm volatile("st.shared.v2.u32 [%0], {%1,%2};" :: "r"(a), "r"(x), "r"(y) : "memory"); }
__device__ __forceinline__ void sts128(uint32_t a, uint4 v) { asm volatile("st.shared.v4.u32 [%0], {%1,%2,%3,%4};" :: "r"(a), "r"(v.x), "r"(v.y), "r"(v.z), "r"(v.w) : "memory"); }
__device__ __forceinline__ int4 ldg_stream(const int4* p) {
    int4 v;
    asm volatile("ld.global.nc.L1::no_allocate.v4.s32 {%0,%1,%2,%3}, [%4];" : "=r"(v.x), "=r"(v.y), "=r"(v.z), "=r"(v.w) : "l"(p));
    return v;
}
__device__ __forceinline__ unsigned ld_acquire(const unsigned* p) {
    unsigned v; asm volatile("ld.acquire.gpu.global.u32 %0, [%1];" : "=r"(v) : "l"(p) : "memory"); return v;
}
__device__ __forceinline__ unsigned ld_relaxed(const unsigned* p) {
    unsigned v; asm volatile("ld.relaxed.gpu.global.u32 %0, [%1];" : "=r"(v) : "l"(p) : "memory"); return v;
}
__device__ __forceinline__ void red_add_release(unsigned* p, unsigned v) {
    asm volatile("red.add.release.gpu.global.u32 [%0], %1;" :: "l"(p), "r"(v) : "memory");
}
__device__ __forceinline__ void wait_counter(const unsigned* p, unsigned target) {
    int it = 0;
    while ((int)(ld_acquire(p) - target) < 0) { if (++it > SPIN_LIMIT) __trap(); }
}
template <int ID, int N> __device__ __forceinline__ void bar_sync() { asm volatile("bar.sync %0, %1;" :: "n"(ID), "n"(N) : "memory"); }
template <int ID, int N> __device__ __forceinline__ void bar_arrive() { asm volatile("bar.arrive %0, %1;" :: "n"(ID), "n"(N) : "memory"); }

__device__ __forceinline__ float bf_lo(uint32_t x) { return __uint_as_float(x << 16); }
__device__ __forceinline__ float bf_hi(uint32_t x) { return __uint_as_float(x & 0xFFFF0000u); }
__device__ __forceinline__ uint32_t pack_bf2(float lo, float hi) {
    uint32_t r; asm("cvt.rn.bf16x2.f32 %0, %1, %2;" : "=r"(r) : "f"(hi), "f"(lo)); return r;
}
__device__ __forceinline__ float rbf(float x) { return bf_hi(pack_bf2(0.f, x)); }
__device__ __forceinline__ uint32_t hmul2_bf(uint32_t a, uint32_t b) {
    uint32_t r; asm("mul.rn.bf16x2 %0, %1, %2;" : "=r"(r) : "r"(a), "r"(b)); return r;
}
__device__ __forceinline__ uint32_t hsub2_bf(uint32_t a, uint32_t b) {
    uint32_t r; asm("sub.rn.bf16x2 %0, %1, %2;" : "=r"(r) : "r"(a), "r"(b)); return r;
}
__device__ __forceinline__ float sqrt_apx(float x) { float r; asm("sqrt.approx.ftz.f32 %0, %1;" : "=f"(r) : "f"(x)); return r; }
__device__ __forceinline__ float rcp_apx(float x) { float r; asm("rcp.approx.ftz.f32 %0, %1;" : "=f"(r) : "f"(x)); return r; }

__device__ __forceinline__ float edge_dist(uint32_t rxy, uint32_t rz  ) {
    uint32_t sq = hmul2_bf(rxy, rxy);
    uint32_t sz = hmul2_bf(rz, rz);
    float ss = rbf((bf_lo(sq) + bf_hi(sq)) + bf_lo(sz));
    ss = rbf(ss + 1e-8f);
    return rbf(sqrt_apx(ss));
}
__device__ __forceinline__ float edge_fcut(float d) {
    float t = rbf(d * 3.14159265358979f);
    t = rbf(t * 0.2f);
    float c = rbf(__cosf(t));
    return 0.5f * rbf(c + 1.0f);
}

__device__ __forceinline__ void load_pos(uint32_t base, int n, uint32_t& xy, uint32_t& z) {
    uint32_t a = base + ((n * 6) & ~3);
    uint32_t w0 = lds32(a), w1 = lds32(a + 4);
    uint32_t sh = (n & 1) << 4;
    xy = __funnelshift_r(w0, w1, sh);
    z = (w1 >> sh) & 0xFFFFu;
}


__device__ __forceinline__ void wg_fence() { asm volatile("wgmma.fence.sync.aligned;" ::: "memory"); }
__device__ __forceinline__ void wg_commit() { asm volatile("wgmma.commit_group.sync.aligned;" ::: "memory"); }
template <int N> __device__ __forceinline__ void wg_wait() { asm volatile("wgmma.wait_group.sync.aligned %0;" :: "n"(N) : "memory"); }
constexpr uint32_t DESC_HI = (1u << 30) | (1024u >> 4);
__device__ __forceinline__ uint32_t desc_lo(uint32_t addr) { return ((addr & 0x3FFFF) >> 4) | (1u << 16); }

#define R8(C, d, o) C(d[o]), C(d[o + 1]), C(d[o + 2]), C(d[o + 3]), C(d[o + 4]), C(d[o + 5]), C(d[o + 6]), C(d[o + 7])
#define WG_PRED_FIRST "setp.ne.b32 p, 0, 0;\n"
#define WG_PRED_ACC   "setp.eq.b32 p, 0, 0;\n"
#define DEF_WG_SS16(NAME, C, PRED)                                                                              \
__device__ __forceinline__ void NAME(float (&d)[8], uint32_t da, uint32_t db) {                                 \
    asm volatile("{\n.reg .pred p;\n.reg .b64 da, db;\n" PRED "mov.b64 da, {%8, %10};\nmov.b64 db, {%9, %10};\n"   \
        "wgmma.mma_async.sync.aligned.m64n16k16.f32.bf16.bf16 {%0,%1,%2,%3,%4,%5,%6,%7}, da, db, p, 1, 1, 1, 1;\n}" \
        : R8(C, d, 0) : "r"(da), "r"(db), "r"(DESC_HI));                                                        \
}
#define DEF_WG_SS48(NAME, C, PRED)                                                                              \
__device__ __forceinline__ void NAME(float (&d)[24], uint32_t da, uint32_t db) {                                \
    asm volatile("{\n.reg .pred p;\n.reg .b64 da, db;\n" PRED "mov.b64 da, {%24, %26};\nmov.b64 db, {%25, %26};\n"  \
        "wgmma.mma_async.sync.aligned.m64n48k16.f32.bf16.bf16 "                                                 \
        "{%0,%1,%2,%3,%4,%5,%6,%7,%8,%9,%10,%11,%12,%13,%14,%15,%16,%17,%18,%19,%20,%21,%22,%23}, da, db, p, 1, 1, 1, 1;\n}" \
        : R8(C, d, 0), R8(C, d, 8), R8(C, d, 16) : "r"(da), "r"(db), "r"(DESC_HI));                             \
}
#define C_OUT "=f"
#define C_IO "+f"
DEF_WG_SS48(wg_ss48_first, C_OUT, WG_PRED_FIRST)
DEF_WG_SS48(wg_ss48_acc, C_IO, WG_PRED_ACC)
DEF_WG_SS16(wg_ss16_first, C_OUT, WG_PRED_FIRST)
DEF_WG_SS16(wg_ss16_acc, C_IO, WG_PRED_ACC)

__device__ __forceinline__ uint32_t radial2(float d, uint32_t f2) {
    const float scale = edge_fcut(d) * rcp_apx(d);
    const uint32_t a = hmul2_bf(pack_bf2(d, d), f2);
    const float a0 = bf_lo(a), a1 = bf_hi(a);
    if (__builtin_expect(fmaxf(fabsf(a0), fabsf(a1)) > 200.f, 0))
        return pack_bf2(sinf(a0) * scale, sinf(a1) * scale);
    return pack_bf2(__sinf(a0) * scale, __sinf(a1) * scale);
}

__device__ __forceinline__ void load_tile(uint32_t tb, const __nv_bfloat16* sv, int tile, int lane) {
    const char* g = (const char*)(sv + (size_t)tile * 16 * 256) + lane * 16;
    const uint32_t d = tb + lane * 16 + (lane >= 8 ? 128 : 0);
#pragma unroll 4
    for (int r = 0; r < 16; r++) cp_async16(d + r * TILE_STRIDE, g + r * 512);
    asm volatile("cp.async.commit_group;" ::: "memory");
}
__device__ __forceinline__ void build_tile(uint32_t sb, uint32_t tb, int tile, int lane) {
    const int g = lane >> 2, t = lane & 3;
    const int m = lane >> 3, r = lane & 7;
    asm volatile("cp.async.wait_group 0;" ::: "memory");
    __syncwarp();
    float acc[8][4];
#pragma unroll
    for (int i = 0; i < 8; i++) { acc[i][0] = acc[i][1] = acc[i][2] = acc[i][3] = 0.f; }
#pragma unroll 1
    for (int ks = 0; ks < 4; ks++) {
        uint32_t a[4];
        ldsm_x4(a, tb + ((m & 1) * 8 + r) * TILE_STRIDE + (ks * 16 + (m >> 1) * 8) * 2);
#pragma unroll
        for (int np = 0; np < 4; np++) {
            uint32_t b[4];
            ldsm_x4_t(b, sb + SM_W1S + (ks * 16 + (m & 1) * 8 + r) * W1STRIDE + (np * 16 + (m >> 1) * 8) * 2);
            mma16816(acc[2 * np], a, b[0], b[1]);
            mma16816(acc[2 * np + 1], a, b[2], b[3]);
        }
    }
    uint32_t hf[4][4];
#pragma unroll
    for (int i = 0; i < 8; i++) {
        float x[4];
#pragma unroll
        for (int k = 0; k < 4; k++) {
            float v = rbf(acc[i][k]);
            x[k] = __fdividef(v, 1.0f + __expf(-v));
        }
        hf[i >> 1][(i & 1) * 2] = pack_bf2(x[0], x[1]);
        hf[i >> 1][(i & 1) * 2 + 1] = pack_bf2(x[2], x[3]);
    }
    __syncwarp();
    uint32_t ph[8][2];
#pragma unroll 1
    for (int bi = 0; bi < 3; bi++) {
        const int col = bi == 0 ? 128 : bi == 1 ? 0 : 64;
#pragma unroll
        for (int i = 0; i < 8; i++) { acc[i][0] = acc[i][1] = acc[i][2] = acc[i][3] = 0.f; }
#pragma unroll
        for (int ks = 0; ks < 4; ks++) {
#pragma unroll
            for (int np = 0; np < 4; np++) {
                uint32_t b[4];
                ldsm_x4_t(b, sb + SM_W2P + (ks * 16 + (m & 1) * 8 + r) * WSTRIDE + (col + np * 16 + (m >> 1) * 8) * 2);
                mma16816(acc[2 * np], hf[ks], b[0], b[1]);
                mma16816(acc[2 * np + 1], hf[ks], b[2], b[3]);
            }
        }
#pragma unroll
        for (int i = 0; i < 8; i++) { ph[i][0] = pack_bf2(acc[i][0], acc[i][1]); ph[i][1] = pack_bf2(acc[i][2], acc[i][3]); }
        if (bi < 2) {
            const uint32_t dcol = bi == 0 ? 128 : 0;
#pragma unroll
            for (int i = 0; i < 8; i++) {
                sts32(tb + g * TILE_STRIDE + dcol + (i * 8 + 2 * t) * 2, ph[i][0]);
                sts32(tb + (g + 8) * TILE_STRIDE + dcol + (i * 8 + 2 * t) * 2, ph[i][1]);
            }
        }
    }
#pragma unroll 1
    for (int c = 0; c < 3; c++) {
        uint2 v[4][2];
#pragma unroll
        for (int w = 0; w < 4; w++) {
            v[w][0] = lds64(tb + g * TILE_STRIDE + (128 + 64 * c + 16 * w + 4 * t) * 2);
            v[w][1] = lds64(tb + (g + 8) * TILE_STRIDE + (128 + 64 * c + 16 * w + 4 * t) * 2);
        }
        __syncwarp();
#pragma unroll
        for (int w = 0; w < 4; w++) {
#pragma unroll
            for (int hh = 0; hh < 2; hh++) {
                uint32_t ev = __byte_perm(v[w][hh].x, v[w][hh].y, 0x5410);
                uint32_t od = __byte_perm(v[w][hh].x, v[w][hh].y, 0x7632);
                uint32_t rowb = tb + (g + 8 * hh) * TILE_STRIDE + (128 + 64 * c + 16 * w + 2 * t) * 2;
                sts32(rowb, hmul2_bf(ph[2 * w][hh], ev));
                sts32(rowb + 16, hmul2_bf(ph[2 * w + 1][hh], od));
            }
        }
    }
    __syncwarp();
    uint4* gt = reinterpret_cast<uint4*>(g_table + (size_t)tile * 16 * 320);
#pragma unroll 4
    for (int it = 0; it < 20; it++) {
        const int f = it * 32 + lane, row = f / 40, ch = f - row * 40;
        gt[f] = lds128(tb + row * TILE_STRIDE + ch * 16);
    }
    __syncwarp();
}

__device__ __noinline__ void slow_path(const Params& P, uint8_t* smem, int q, int nlocal) {
    float* accX = reinterpret_cast<float*>(smem + 65536);
    float* accU = accX + 4096;
    float* coef = accU + 3072;
    uint2* queue = reinterpret_cast<uint2*>(coef + 64);
    int* misc = reinterpret_cast<int*>(smem + SM_MISC);
    const uint32_t sb = smem_u32(smem);
    const int tid = threadIdx.x;
    for (int nl = 0; nl < nlocal; nl++) {
        const int node = q * P.nper + nl;
        for (int i = tid; i < 4096 + 3072; i += NT) accX[i] = 0.f;
        if (tid == 0) misc[MISC_QN] = 0;
        __syncthreads();
        for (int base = 0; base < EE; base += NT) {
            const int f = base + tid;
            bool hit = false;
            if (f < EE && P.dst[f] == node) {
                const int s = P.src[f];
                uint32_t sxy, sz, dxy, dz;
                load_pos(sb + SM_POS, s, sxy, sz);
                load_pos(sb + SM_POS, node, dxy, dz);
                const uint32_t rxy = hsub2_bf(sxy, dxy), rz = hsub2_bf(sz, dz) & 0xFFFF;
                if (edge_dist(rxy, rz) < 5.0f) {
                    hit = true;
                    int sl = atomicAdd(&misc[MISC_QN], 1);
                    queue[sl] = make_uint2((uint32_t)s | (rxy << 16), (rxy >> 16) | (rz << 16));
                }
            }
            if (!__syncthreads_or(hit)) continue;
            const int qn = misc[MISC_QN];
            for (int k = 0; k < qn; k++) {
                uint2 en = queue[k];
                if (tid < 64) {
                    uint32_t rxy = (en.x >> 16) | (en.y << 16), rz = en.y >> 16;
                    float d = edge_dist(rxy, rz);
                    float inv = 1.0f / d;
                    float f = __bfloat162float(P.freqs[tid & 15]);
                    float cf = rbf(sinf(rbf(d * f)) * (edge_fcut(d) * inv));
                    int c = tid >> 4;
                    float mult = c == 0 ? 1.f : rbf((c == 1 ? bf_lo(rxy) : c == 2 ? bf_hi(rxy) : bf_lo(rz)) * inv);
                    coef[tid] = rbf(cf * mult);
                }
                __syncthreads();
                const unsigned short* row = reinterpret_cast<const unsigned short*>(g_table) + (size_t)(en.x & 0xFFFF) * 320;
                for (int i = tid; i < 4096; i += NT) accX[i] += coef[i >> 6] * bf_lo(__ldcg(row + (i < 1024 ? 0 : 64) + (i & 63)));
                for (int i = tid; i < 3072; i += NT) accU[i] += coef[i / 192] * bf_lo(__ldcg(row + 128 + i % 192));
                __syncthreads();
            }
            if (tid == 0) misc[MISC_QN] = 0;
            __syncthreads();
        }
        if (tid < 256) {
            const int c = tid >> 6, j = tid & 63;
            const int col0 = c == 0 ? 0 : 128;
            const int p = (j & ~15) + 8 * (j & 1) + ((j & 15) >> 1);
            float o = 0.f;
            for (int k = 0; k < 16; k++) {
                o += accX[(c * 16 + k) * 64 + p] * __bfloat162float(P.wr[k * 192 + col0 + j]);
                if (c > 0) o += accU[k * 192 + (c - 1) * 64 + p] * __bfloat162float(P.wr[k * 192 + 64 + j]);
            }
            P.out[(size_t)node * 256 + tid] = __float2bfloat16(o + __bfloat162float(P.sv[(size_t)node * 256 + tid]));
        }
        __syncthreads();
    }
}

__global__ void __launch_bounds__(NT, 1) painn_kernel(const __grid_constant__ Params P) {
    extern __shared__ uint8_t smem_raw[];
    uint8_t* smem = smem_raw + ((1024 - (smem_u32(smem_raw) & 1023)) & 1023);
    const uint32_t sb = smem_u32(smem);
    const int tid = threadIdx.x, lane = tid & 31;
    const int wu = __shfl_sync(0xffffffffu, tid >> 5, 0);
    const int q = blockIdx.x, nP = gridDim.x;
    int* hist = reinterpret_cast<int*>(smem + SM_HIST);
    int* cnt = reinterpret_cast<int*>(smem + SM_CNT);
    int* misc = reinterpret_cast<int*>(smem + SM_MISC);
    uint32_t* glist = reinterpret_cast<uint32_t*>(smem + SM_GL);
    const uint32_t bar_full = sb + SM_BAR, bar_empty = bar_full + 96;
    const uint32_t bar_pos = bar_full + 192, bar_in = bar_full + 200;
    const int nlocal = max(0, min(P.nper, NN - q * P.nper));
    int4 s4[4], d4[4];
    if (wu < NEWW) {
        const int i0 = q * P.e4q, i1 = min(i0 + P.e4q, EE / 4);
#pragma unroll
        for (int u = 0; u < 4; u++) {
            int idx = i0 + tid + u * NEW_;
            d4[u] = make_int4(-1, -1, -1, -1); s4[u] = make_int4(0, 0, 0, 0);
            if (idx < i1) {
                d4[u] = ldg_stream(reinterpret_cast<const int4*>(P.dst) + idx);
                s4[u] = ldg_stream(reinterpret_cast<const int4*>(P.src) + idx);
            }
        }
    } else if (tid == NT - 1) {
        for (int i = 0; i < 2 * NSLOT; i++) { mbar_init(bar_full + i * 8, 33); mbar_init(bar_empty + i * 8, 4); }
        mbar_init(bar_pos, 1);
        mbar_init(bar_in, 1);
        misc[MISC_OVF] = P.mode == 2; misc[MISC_ROVF] = P.mode == 1; misc[MISC_GSPLIT] = 0; misc[MISC_NSPLIT] = 0;
        fence_proxy_async();
        asm volatile("mbarrier.arrive.expect_tx.shared.b64 _, [%0], %1;" :: "r"(bar_pos), "r"(NN * 6) : "memory");
        asm volatile("cp.async.bulk.shared::cluster.global.mbarrier::complete_tx::bytes [%0], [%1], %2, [%3];"
                     :: "r"(sb + SM_POS), "l"(P.pos), "r"(NN * 6), "r"(bar_pos) : "memory");
    }
    unsigned cnt0 = 0;
    if (tid == 0 || tid == NT - 32) cnt0 = ld_relaxed(tid == 0 ? &g_barA : &g_barB);
    if (tid < MAXP) hist[tid] = 1;
    if (tid < 132) cnt[tid] = 0;
    __syncthreads();
    if (wu < NEWW) {
        mbar_wait(bar_pos, 0);
#pragma unroll 1
        for (int u = 0; u < 2; u++) {
            const int dd[8] = {d4[0].x, d4[0].y, d4[0].z, d4[0].w, d4[1].x, d4[1].y, d4[1].z, d4[1].w};
            const int ss[8] = {s4[0].x, s4[0].y, s4[0].z, s4[0].w, s4[1].x, s4[1].y, s4[1].z, s4[1].w};
            bool ok[8];
#pragma unroll
            for (int k = 0; k < 8; k++) {
                uint32_t sxy, sz, dxy, dz;
                load_pos(sb + SM_POS, ss[k], sxy, sz);
                load_pos(sb + SM_POS, max(dd[k], 0), dxy, dz);
                const uint32_t rxy = hsub2_bf(sxy, dxy), rz = hsub2_bf(sz, dz);
                const uint32_t sq = hmul2_bf(rxy, rxy), sqz = hmul2_bf(rz, rz);
                ok[k] = dd[k] >= 0 && rbf((bf_lo(sq) + bf_hi(sq)) + bf_lo(sqz)) <= 24.75f;
            }
            uint32_t own[8], slot[8];
#pragma unroll
            for (int k = 0; k < 8; k++) {
                own[k] = __umulhi((uint32_t)max(dd[k], 0), P.magic);
                slot[k] = ok[k] ? atomicAdd(&hist[own[k]], 1) : CAPR;
            }
#pragma unroll
            for (int k = 0; k < 8; k++)
                if (slot[k] < CAPR) sts32(sb + SM_RUNS + own[k] * RUNB + slot[k] * 4, (uint32_t)ss[k] | ((dd[k] - own[k] * P.nper) << 16));
            d4[0] = d4[2]; d4[1] = d4[3]; s4[0] = s4[2]; s4[1] = s4[3];
        }
        bar_sync<4, NEW_>();
        {
            const int nch = nP * (RUNB / 16);
#pragma unroll
            for (int k = 0; k < (MAXP * (RUNB / 16) + NEW_ - 1) / NEW_; k++) {
                const int f = tid + k * NEW_;
                if (f < nch) {
                    const int r = f / (RUNB / 16), ch = f - r * (RUNB / 16);
                    uint4 v = lds128(sb + SM_RUNS + f * 16);
                    if (ch == 0) v.x = hist[r] - 1;
                    reinterpret_cast<uint4*>(g_stage + ((size_t)r * nP + q) * CAPR)[ch] = v;
                }
            }
        }
        bar_sync<4, NEW_>();
        if (tid == 0) red_add_release(&g_barA, 1);
        bar_sync<4, NEW_>();
        if (tid >= 32) {
            if (tid - 32 < nlocal && P.mode != 2) {
                uint32_t xy, z;
                load_pos(sb + SM_POS, q * P.nper + tid - 32, xy, z);
                sts64(sb + SM_GL + (tid - 32) * 8, xy, z);
            }
            const uint32_t f2 = __ldg(reinterpret_cast<const uint32_t*>(P.freqs) + (tid & 7));
#pragma unroll 2
            for (int i = tid - 32; i < LUT_N * 8; i += NEW_ - 32)
                sts32(sb + SM_LUT + i * 4, radial2(__uint_as_float((uint32_t)(LUT_BASE + (i >> 3)) << 16), f2));
        }
        if (tid == 0) {
            wait_counter(&g_barA, (cnt0 / (unsigned)nP + 1) * (unsigned)nP);
            asm volatile("fence.proxy.async;" ::: "memory");
            asm volatile("mbarrier.arrive.expect_tx.shared.b64 _, [%0], %1;" :: "r"(bar_in), "r"(nP * RUNB) : "memory");
            asm volatile("cp.async.bulk.shared::cluster.global.mbarrier::complete_tx::bytes [%0], [%1], %2, [%3];"
                         :: "r"(sb + SM_RUNS), "l"(g_stage + (size_t)q * nP * CAPR), "r"(nP * RUNB), "r"(bar_in) : "memory");
        }
    } else {
        const int tw = wu - NEWW, tt = tid - NEW_;
        for (int i = tt; i < 512; i += 160)
            cp_async16(sb + SM_W1S + (i >> 3) * W1STRIDE + (i & 7) * 16, reinterpret_cast<const char*>(P.w1) + i * 16);
        asm volatile("cp.async.commit_group;" ::: "memory");
#pragma unroll 1
        for (int u0 = 0; u0 < 6; u0 += 3) {
            uint4 x[3][2];
#pragma unroll
            for (int u = 0; u < 3; u++) {
                const int item = tt + (u0 + u) * 160;
                const __nv_bfloat16* g = item < 768 ? P.w2 + item * 16 : P.wr + (item - 768) * 16;
                x[u][0] = __ldg(reinterpret_cast<const uint4*>(g));
                x[u][1] = __ldg(reinterpret_cast<const uint4*>(g) + 1);
            }
            if (u0 == 3) {
                if (q + nP * tw < NTILES) load_tile(sb + SM_TILE + tw * TILE_BYTES, P.sv, q + nP * tw, lane);
            }
#pragma unroll
            for (int u = 0; u < 3; u++) {
                const int item = tt + (u0 + u) * 160;
                const int row = item / 12, blk = item - row * 12;
                const uint32_t a = sb + SM_W2P + row * WSTRIDE + blk * 32;
                uint4 ev, od;
                ev.x = __byte_perm(x[u][0].x, x[u][0].y, 0x5410); od.x = __byte_perm(x[u][0].x, x[u][0].y, 0x7632);
                ev.y = __byte_perm(x[u][0].z, x[u][0].w, 0x5410); od.y = __byte_perm(x[u][0].z, x[u][0].w, 0x7632);
                ev.z = __byte_perm(x[u][1].x, x[u][1].y, 0x5410); od.z = __byte_perm(x[u][1].x, x[u][1].y, 0x7632);
                ev.w = __byte_perm(x[u][1].z, x[u][1].w, 0x5410); od.w = __byte_perm(x[u][1].z, x[u][1].w, 0x7632);
                sts128(a, ev); sts128(a + 16, od);
            }
        }
        asm volatile("cp.async.wait_group 1;" ::: "memory");
        bar_sync<5, 160>();
#pragma unroll 1
        for (int tile = q + nP * tw; tile < NTILES; tile += nP * NTILEW) {
            build_tile(sb, sb + SM_TILE + tw * TILE_BYTES, tile, lane);
            if (lane == 0) red_add_release(&g_barB, 1);
            if (tile + nP * NTILEW < NTILES) load_tile(sb + SM_TILE + tw * TILE_BYTES, P.sv, tile + nP * NTILEW, lane);
        }
    }
    __syncthreads();
    mbar_wait(bar_pos, 0);
    mbar_wait(bar_in, 0);
    if (wu < 15 && P.mode == 0) {
        bool ovf = false, rovf = false;
#pragma unroll 1
        for (int r0 = wu; r0 < nP; r0 += 15 * 9) {
            uint32_t e[9], rxy[9], rz[9];
            int n[9], slot[9];
            int nmax = 0;
#pragma unroll
            for (int u = 0; u < 9; u++) {
                const int r = min(r0 + 15 * u, nP - 1);
                n[u] = r0 + 15 * u < nP ? (int)lds32(sb + SM_RUNS + r * RUNB) : 0;
                e[u] = lds32(sb + SM_RUNS + r * RUNB + (1 + lane) * 4);
            }
#pragma unroll
            for (int u = 0; u < 9; u++) {
                nmax = max(nmax, n[u]);
                if (lane >= n[u]) e[u] = 0;
                uint32_t sxy, sz;
                load_pos(sb + SM_POS, e[u] & 0xFFFF, sxy, sz);
                const uint2 dp = lds64(sb + SM_GL + (e[u] >> 16) * 8);
                rxy[u] = hsub2_bf(sxy, dp.x); rz[u] = hsub2_bf(sz, dp.y);
            }
#pragma unroll
            for (int u = 0; u < 9; u++) slot[u] = lane < n[u] ? atomicAdd(&cnt[e[u] >> 16], 1) : 0;
#pragma unroll
            for (int u = 0; u < 9; u++) {
                if (lane < n[u]) {
                    if (slot[u] < P.capn)
                        sts64(sb + SM_BKT + ((e[u] >> 16) * P.capn + slot[u]) * 8, (e[u] & 0xFFFF) | (rxy[u] << 16), (rxy[u] >> 16) | (rz[u] << 16));
                    else ovf = true;
                }
            }
            rovf |= nmax >= CAPR;
            if (nmax > 32) {
#pragma unroll 1
                for (int u = 0; u < 9; u++) {
                    const int r = r0 + 15 * u;
                    if (r >= nP) break;
                    const int nn = min((int)lds32(sb + SM_RUNS + r * RUNB), CAPR - 1);
                    for (int i = 33 + lane; i <= nn; i += 32) {
                        const uint32_t ee = lds32(sb + SM_RUNS + r * RUNB + i * 4);
                        uint32_t sxy, sz;
                        load_pos(sb + SM_POS, ee & 0xFFFF, sxy, sz);
                        const uint2 dp = lds64(sb + SM_GL + (ee >> 16) * 8);
                        const uint32_t axy = hsub2_bf(sxy, dp.x), az = hsub2_bf(sz, dp.y);
                        const int sl = atomicAdd(&cnt[ee >> 16], 1);
                        if (sl < P.capn) sts64(sb + SM_BKT + ((ee >> 16) * P.capn + sl) * 8, (ee & 0xFFFF) | (axy << 16), (axy >> 16) | (az << 16));
                        else ovf = true;
                    }
                }
            }
        }
        if (ovf) misc[MISC_OVF] = 1;
        if (rovf) misc[MISC_ROVF] = 1;
    } else if (wu == 15 && lane == 0) {
        wait_counter(&g_barB, (cnt0 / (unsigned)NTILES + 1) * (unsigned)NTILES);
    }
    __syncthreads();
    if (misc[MISC_ROVF]) {
        __syncthreads();
        if (tid < 132) cnt[tid] = 0;
        if (tid == 0) misc[MISC_OVF] = 0;
        __syncthreads();
        const int node0 = q * P.nper;
        bool ovf = false;
#pragma unroll 1
        for (int i = tid; i < EE / 4; i += NT) {
            const int4 d4r = __ldg(reinterpret_cast<const int4*>(P.dst) + i);
            const int dd[4] = {d4r.x, d4r.y, d4r.z, d4r.w};
#pragma unroll 1
            for (int k = 0; k < 4; k++) {
                const unsigned dl = (unsigned)(dd[k] - node0);
                if (dl < (unsigned)nlocal) {
                    const int s = __ldg(P.src + i * 4 + k);
                    uint32_t sxy, sz;
                    load_pos(sb + SM_POS, s, sxy, sz);
                    const uint2 dp = lds64(sb + SM_GL + dl * 8);
                    const uint32_t rxy = hsub2_bf(sxy, dp.x), rz = hsub2_bf(sz, dp.y);
                    const uint32_t sq = hmul2_bf(rxy, rxy), sqz = hmul2_bf(rz, rz);
                    if (rbf((bf_lo(sq) + bf_hi(sq)) + bf_lo(sqz)) <= 24.75f) {
                        const int sl = atomicAdd(&cnt[dl], 1);
                        if (sl < P.capn) sts64(sb + SM_BKT + (dl * P.capn + sl) * 8, (uint32_t)s | (rxy << 16), (rxy >> 16) | (rz << 16));
                        else ovf = true;
                    }
                }
            }
        }
        if (ovf) misc[MISC_OVF] = 1;
        __syncthreads();
    }
    if (misc[MISC_OVF]) {
        slow_path(P, smem, q, nlocal);
        return;
    }
    {
        int c = 0, G = 0, inc = 0;
        if (wu < 4) {
            c = tid < nlocal ? cnt[tid] : 0;
            G = tid < nlocal ? max(1, (c + 15) >> 4) : 0;
            inc = G;
#pragma unroll
            for (int o = 1; o < 32; o <<= 1) { int y = __shfl_up_sync(0xffffffffu, inc, o); if (lane >= o) inc += y; }
            if (lane == 31) misc[MISC_WT2 + wu] = inc;
        }
        __syncthreads();
        if (wu < 4) {
            int w0 = misc[MISC_WT2], w1 = misc[MISC_WT2 + 1], w2 = misc[MISC_WT2 + 2], w3 = misc[MISC_WT2 + 3];
            int gtot = w0 + w1 + w2 + w3;
            int gpre = inc - G + (wu > 0 ? w0 : 0) + (wu > 1 ? w1 : 0) + (wu > 2 ? w2 : 0);
            for (int g = 0; g < G; g++)
                glist[gpre + g] = (uint32_t)(tid * P.capn + 16 * g) | ((uint32_t)min(16, c - 16 * g) << 16);
            int half = gtot >> 1;
            if (G > 0 && gpre <= half && half < gpre + G) {
                const bool before = half - gpre <= gpre + G - half;
                misc[MISC_GSPLIT] = before ? gpre : gpre + G;
                misc[MISC_NSPLIT] = before ? tid : tid + 1;
            }
            if (tid == 0) misc[MISC_GTOT] = gtot;
            cnt[tid] = G;
        }
        __syncthreads();
    }
    const int gsplit = misc[MISC_GSPLIT], gtot = misc[MISC_GTOT], nsplit = misc[MISC_NSPLIT];
    const int g = lane >> 2, t = lane & 3, m = lane >> 3, r = lane & 7;
    const bool tb0 = t & 1, tb1 = t & 2;
#define FENCE_REGS8(x, o) asm volatile("" : "+f"(x[o]), "+f"(x[o + 1]), "+f"(x[o + 2]), "+f"(x[o + 3]), "+f"(x[o + 4]), "+f"(x[o + 5]), "+f"(x[o + 6]), "+f"(x[o + 7]) :: "memory")
#define QUAD_REDUCE(v, o0, o1)                                                                          \
    {                                                                                                   \
        float k4[4];                                                                                    \
        _Pragma("unroll")                                                                               \
        for (int i = 0; i < 4; i++)                                                                     \
            k4[i] = (tb0 ? v[4 + i] : v[i]) + __shfl_xor_sync(0xffffffffu, tb0 ? v[i] : v[4 + i], 1);   \
        o0 = (tb1 ? k4[2] : k4[0]) + __shfl_xor_sync(0xffffffffu, tb1 ? k4[0] : k4[2], 2);              \
        o1 = (tb1 ? k4[3] : k4[1]) + __shfl_xor_sync(0xffffffffu, tb1 ? k4[1] : k4[3], 2);              \
    }
    if (wu >= 8) {
        if (wu >= 14) return;
        const int team = wu >= 11 ? 1 : 0, pw = wu - 8 - 3 * team;
        const int gbeg = team == 0 ? 0 : gsplit, gcount = (team == 0 ? gsplit : gtot) - gbeg;
        const int e = lane & 15, hb = lane >> 4;
        const char* lane_src = reinterpret_cast<const char*>(g_table) + lane * 16;
        const char* lane_src5 = reinterpret_cast<const char*>(g_table) + 512 + (lane & 7) * 16;
        asm volatile("" : "+l"(lane_src), "+l"(lane_src5));
        const int s0 = team * NSLOT + pw * 2;
        const uint32_t x7 = (lane & 7) << 4;
        const uint32_t rowb = sb + SM_RING + s0 * SLOTB + (lane >> 3) * 2048;
        const uint32_t row5 = sb + SM_RING + s0 * SLOTB + 4 * 2048 + (lane >> 3) * 128;
        const uint32_t x5a = x7 ^ ((lane >> 3) << 4), x5b = x7 ^ (((lane >> 3) + 4) << 4);
        const uint32_t cb = sb + SM_COEF + (s0 + hb) * 2048 + e * 128;
        const uint32_t cx = (e & 7) << 4;
        const uint32_t csr_lane = sb + SM_BKT + e * 8;
        const uint32_t fullA = bar_full + s0 * 8, emptyA = bar_empty + s0 * 8;
        bar_sync<3, 448>();
        uint32_t par = 1;
        for (int gA = 2 * pw; gA < gcount; gA += NSLOT) {
            const bool hasB = gA + 1 < gcount;
            uint32_t info = 0;
            if (gA + hb < gcount) info = glist[gbeg + gA + hb];
            const bool valid = e < (int)(info >> 16);
            uint2 en = make_uint2(0u, 0u);
            if (valid) en = lds64(csr_lane + (info & 0xFFFF) * 8);
            const uint32_t rxy = (en.x >> 16) | (en.y << 16), rz = en.y >> 16;
            const float d = edge_dist(rxy, rz);
            uint4 ca = make_uint4(0u, 0u, 0u, 0u), cb4 = ca;
            const int li = (int)(__float_as_uint(d) >> 16) - LUT_BASE;
            if (valid && li >= 0) { ca = lds128(sb + SM_LUT + li * 32); cb4 = lds128(sb + SM_LUT + li * 32 + 16); }
            if (__any_sync(0xffffffffu, valid && li < 0)) {
                if (valid && li < 0) {
                    const uint32_t* fp = reinterpret_cast<const uint32_t*>(P.freqs);
                    uint32_t o[8];
#pragma unroll 1
                    for (int p = 0; p < 8; p++) {
                        const uint32_t c2 = radial2(d, __ldg(fp + p));
#pragma unroll
                        for (int x = 0; x < 7; x++) o[x] = o[x + 1];
                        o[7] = c2;
                    }
                    ca = make_uint4(o[0], o[1], o[2], o[3]); cb4 = make_uint4(o[4], o[5], o[6], o[7]);
                }
            }
            const float inv = rcp_apx(d);
            const float hx = bf_lo(rxy) * inv, hy = bf_hi(rxy) * inv, hz = bf_lo(rz) * inv;
            const uint32_t hx2 = pack_bf2(hx, hx), hy2 = pack_bf2(hy, hy), hz2 = pack_bf2(hz, hz);
            const uint32_t srcn = valid ? (en.x & 0xFFFF) : 0xFFFFFFFFu;
            const unsigned vmask = __ballot_sync(0xffffffffu, valid);
#pragma unroll
            for (int hh = 0; hh < 2; hh++) {
                if (hh == 1 && !hasB) break;
                mbar_wait(emptyA + hh * 8, par);
                const unsigned gm = (vmask >> (16 * hh)) & 0xFFFFu;
                if (gm == 0xFFFFu) {
#pragma unroll
                    for (int rr = 0; rr < 16; rr++) {
                        const uint32_t s = __shfl_sync(0xffffffffu, srcn, 16 * hh + rr);
                        cp_async16(rowb + hh * SLOTB + rr * 128 + (x7 ^ ((rr & 7) << 4)), lane_src + (size_t)s * ROWB);
                    }
#pragma unroll
                    for (int j = 0; j < 4; j++) {
                        const uint32_t s = __shfl_sync(0xffffffffu, srcn, 16 * hh + 4 * j + (lane >> 3));
                        cp_async16(row5 + hh * SLOTB + j * 512 + ((j & 1) ? x5b : x5a), lane_src5 + (size_t)s * ROWB);
                    }
                } else if (gA >= NSLOT) {
#pragma unroll
                    for (int rr = 0; rr < 16; rr++) {
                        const uint32_t s = __shfl_sync(0xffffffffu, srcn, 16 * hh + rr);
                        cp_async16_valid(rowb + hh * SLOTB + rr * 128 + (x7 ^ ((rr & 7) << 4)), lane_src + (size_t)s * ROWB, s);
                    }
#pragma unroll
                    for (int j = 0; j < 4; j++) {
                        const uint32_t s = __shfl_sync(0xffffffffu, srcn, 16 * hh + 4 * j + (lane >> 3));
                        cp_async16_valid(row5 + hh * SLOTB + j * 512 + ((j & 1) ? x5b : x5a), lane_src5 + (size_t)s * ROWB, s);
                    }
                } else {
#pragma unroll 1
                    for (int rr = 0; rr < 16; rr++) {
                        const uint32_t s = __shfl_sync(0xffffffffu, srcn, 16 * hh + rr);
                        const bool ok = s != 0xFFFFFFFFu;
                        cp_async16_zfill(rowb + hh * SLOTB + rr * 128 + (x7 ^ ((rr & 7) << 4)), lane_src + (size_t)(ok ? s : 0u) * ROWB, ok ? 16 : 0);
                    }
#pragma unroll 1
                    for (int j = 0; j < 4; j++) {
                        const uint32_t s = __shfl_sync(0xffffffffu, srcn, 16 * hh + 4 * j + (lane >> 3));
                        const bool ok = s != 0xFFFFFFFFu;
                        cp_async16_zfill(row5 + hh * SLOTB + j * 512 + ((j & 1) ? x5b : x5a), lane_src5 + (size_t)(ok ? s : 0u) * ROWB, ok ? 16 : 0);
                    }
                }
                cp_async_arrive_noinc(fullA + hh * 8);
            }
            if (hb == 0 || hasB) {
                sts128(cb + cx, ca);
                sts128(cb + (cx ^ 0x10), cb4);
                sts128(cb + (cx ^ 0x20), make_uint4(hmul2_bf(ca.x, hx2), hmul2_bf(ca.y, hx2), hmul2_bf(ca.z, hx2), hmul2_bf(ca.w, hx2)));
                sts128(cb + (cx ^ 0x30), make_uint4(hmul2_bf(cb4.x, hx2), hmul2_bf(cb4.y, hx2), hmul2_bf(cb4.z, hx2), hmul2_bf(cb4.w, hx2)));
                sts128(cb + (cx ^ 0x40), make_uint4(hmul2_bf(ca.x, hy2), hmul2_bf(ca.y, hy2), hmul2_bf(ca.z, hy2), hmul2_bf(ca.w, hy2)));
                sts128(cb + (cx ^ 0x50), make_uint4(hmul2_bf(cb4.x, hy2), hmul2_bf(cb4.y, hy2), hmul2_bf(cb4.z, hy2), hmul2_bf(cb4.w, hy2)));
                sts128(cb + (cx ^ 0x60), make_uint4(hmul2_bf(ca.x, hz2), hmul2_bf(ca.y, hz2), hmul2_bf(ca.z, hz2), hmul2_bf(ca.w, hz2)));
                sts128(cb + (cx ^ 0x70), make_uint4(hmul2_bf(cb4.x, hz2), hmul2_bf(cb4.y, hz2), hmul2_bf(cb4.z, hz2), hmul2_bf(cb4.w, hz2)));
            }
            fence_proxy_async();
            __syncwarp();
            mbar_arrive_elect(fullA);
            if (hasB) mbar_arrive_elect(fullA + 8);
            par ^= 1;
        }
    } else {
        const int team = wu >> 2, w = wu & 3;
        int node = team == 0 ? 0 : nsplit;
        const int nend = team == 0 ? nsplit : nlocal;
        float xs[8], xu[8], xv[8];
        {
            uint32_t a[4], b[4], c[4];
            ldsm_x4_t(a, sb + SM_WRP + ((m >> 1) * 8 + r) * WSTRIDE + (w * 16 + (m & 1) * 8) * 2);
            ldsm_x4_t(b, sb + SM_WRP + ((m >> 1) * 8 + r) * WSTRIDE + (64 + w * 16 + (m & 1) * 8) * 2);
            ldsm_x4_t(c, sb + SM_WRP + ((m >> 1) * 8 + r) * WSTRIDE + (128 + w * 16 + (m & 1) * 8) * 2);
            bar_arrive<3, 448>();
#pragma unroll
            for (int i = 0; i < 4; i++) {
                xs[2 * i] = bf_lo(a[i]); xs[2 * i + 1] = bf_hi(a[i]);
                xu[2 * i] = bf_lo(b[i]); xu[2 * i + 1] = bf_hi(b[i]);
                xv[2 * i] = bf_lo(c[i]); xv[2 * i + 1] = bf_hi(c[i]);
            }
        }
        const uint32_t drows = desc_lo(sb + SM_RING + team * NSLOT * SLOTB);
        const uint32_t dcoef = desc_lo(sb + SM_COEF + team * NSLOT * 2048);
        const int cc = 2 * (t & 1) + (t >> 1);
        const size_t io0 = ((size_t)q * P.nper + node) * 128 + cc * 32 + w * 8 + g;
        const uint32_t* resp = reinterpret_cast<const uint32_t*>(P.sv) + io0;
        uint32_t* outp = reinterpret_cast<uint32_t*>(P.out) + io0;
        const uint32_t fullb = bar_full + team * NSLOT * 8, emptyb = bar_empty + team * NSLOT * 8;
        uint32_t sl = 0, ph = 0;
#define G1_STEP(W48, W16)                                                                               \
        {                                                                                               \
            mbar_wait(fullb + sl * 8, ph);                                                                  \
            const uint32_t dr = drows + sl * (SLOTB / 16), dc = dcoef + sl * 128;                       \
            wg_fence();                                                                                 \
            W48(dv, dr + 128, dc + 2);                                                                  \
            W16(ds, dr, dc);                                                                            \
            W16(u0, dr + 256, dc);                                                                      \
            W16(u1, dr + 384, dc);                                                                      \
            W16(u2, dr + 512, dc);                                                                      \
            wg_commit();                                                                                \
        }
        for (; node < nend; node++) {
            const int G = __shfl_sync(0xffffffffu, cnt[node], 0);
            const uint32_t res = __ldg(resp);
            float ds[8], dv[24], u0[8], u1[8], u2[8];
            G1_STEP(wg_ss48_first, wg_ss16_first)
            uint32_t last = sl;
            sl = sl == NSLOT - 1 ? 0 : sl + 1; ph ^= (sl == 0 ? 1u : 0u);
            for (int gi = 1; gi < G; gi++) {
                G1_STEP(wg_ss48_acc, wg_ss16_acc)
                wg_wait<1>();
                mbar_arrive_elect(emptyb + last * 8);
                last = sl;
                sl = sl == NSLOT - 1 ? 0 : sl + 1; ph ^= (sl == 0 ? 1u : 0u);
            }
            wg_wait<0>();
            mbar_arrive_elect(emptyb + last * 8);
            FENCE_REGS8(ds, 0); FENCE_REGS8(dv, 0); FENCE_REGS8(dv, 8); FENCE_REGS8(dv, 16);
            FENCE_REGS8(u0, 0); FENCE_REGS8(u1, 0); FENCE_REGS8(u2, 0);
            float v[8];
            v[0] = ds[0] * xs[0] + ds[1] * xs[1] + ds[4] * xs[4] + ds[5] * xs[5];
            v[1] = ds[2] * xs[2] + ds[3] * xs[3] + ds[6] * xs[6] + ds[7] * xs[7];
#define VPART(c, U)                                                                                     \
            v[2 + 2 * c] = dv[8 * c] * xv[0] + dv[8 * c + 1] * xv[1] + dv[8 * c + 4] * xv[4] + dv[8 * c + 5] * xv[5] \
                         + U[0] * xu[0] + U[1] * xu[1] + U[4] * xu[4] + U[5] * xu[5];                   \
            v[3 + 2 * c] = dv[8 * c + 2] * xv[2] + dv[8 * c + 3] * xv[3] + dv[8 * c + 6] * xv[6] + dv[8 * c + 7] * xv[7] \
                         + U[2] * xu[2] + U[3] * xu[3] + U[6] * xu[6] + U[7] * xu[7];
            VPART(0, u0) VPART(1, u1) VPART(2, u2)
#undef VPART
            float o0, o1;
            QUAD_REDUCE(v, o0, o1)
            *outp = pack_bf2(o0 + bf_lo(res), o1 + bf_hi(res));
            outp += 128; resp += 128;
        }
#undef G1_STEP
    }
#undef QUAD_REDUCE
#undef FENCE_REGS8
}

}

extern "C" void kernel_launch(void* const* d_in, const int* in_sizes, int n_in, void* d_out, int out_size) {
    (void)in_sizes; (void)n_in; (void)out_size;
    static int nP = 0;
    if (nP == 0) {
        int dev = 0, sms = 0;
        cudaGetDevice(&dev);
        cudaDeviceGetAttribute(&sms, cudaDevAttrMultiProcessorCount, dev);
        nP = sms < MAXP ? sms : MAXP;
        cudaFuncSetAttribute(painn_kernel, cudaFuncAttributeMaxDynamicSharedMemorySize, SM_ALLOC);
    }
    Params P;
    P.sv = (const __nv_bfloat16*)d_in[0];
    P.pos = (const __nv_bfloat16*)d_in[1];
    P.src = (const int*)d_in[2];
    P.dst = (const int*)d_in[3];
    P.freqs = (const __nv_bfloat16*)d_in[4];
    P.w1 = (const __nv_bfloat16*)d_in[5];
    P.w2 = (const __nv_bfloat16*)d_in[6];
    P.wr = (const __nv_bfloat16*)d_in[7];
    P.out = (__nv_bfloat16*)d_out;
    P.nper = (NN + nP - 1) / nP;
    P.magic = (unsigned)(((1ull << 32) + P.nper - 1) / P.nper);
    P.e4q = (EE / 4 + nP - 1) / nP;
    P.capn = (BKT_ENTRIES / P.nper) & ~15;
    if (P.capn > 96) P.capn = 96;
    P.mode = P.nper > 128 ? 2 : P.e4q > 4 * NEW_ ? 1 : 0;
    cudaLaunchConfig_t cfg = {};
    cfg.gridDim = dim3(nP);
    cfg.blockDim = dim3(NT);
    cfg.dynamicSmemBytes = SM_ALLOC;
    cfg.stream = cudaStreamPerThread;
    cudaLaunchAttribute attr[1];
    attr[0].id = cudaLaunchAttributeCooperative;
    attr[0].val.cooperative = 1;
    cfg.attrs = attr;
    cfg.numAttrs = 1;
    cudaLaunchKernelEx(&cfg, painn_kernel, P);
}
```
